```python
import torch

def _softmax(x, axis=-1):
    return torch.softmax(x, dim=axis)
def _gelu(x):
    return torch.nn.functional.gelu(x, approximate="tanh")
def _silu(x):
    return torch.nn.functional.silu(x)
def _sigmoid(x):
    return torch.sigmoid(x)
def _layernorm(x, axis=-1, eps=1e-5):
    m = x.mean(dim=axis, keepdim=True)
    v = x.var(dim=axis, keepdim=True, unbiased=False)
    return (x - m) / torch.sqrt(v + eps)
def _scatter_add(tgt, idx, src, axis=0):
    return tgt.clone().index_add_(axis, idx, src)
def _segment_sum(src, seg, n):
    out = torch.zeros((n,) + src.shape[1:], dtype=src.dtype)
    return out.index_add_(0, seg, src)
def _pad(x, pw):
    flat = tuple(v for pair in reversed(pw) for v in pair)
    return torch.nn.functional.pad(x, flat)

kernel_name = 'gated_mix__sliding_block_cached__mixer_channel_mlp__decode'

def setup_inputs():

    _w = (lambda a: (lambda t: t.to(torch.bfloat16) if t.is_floating_point() else t)(torch.as_tensor(a)))
    def _A_setup():
        B, Sq, D = 8, 1, 448
        Hq, Hkv, Sk, Dh = 16, 8, 4096, 256
        assert Hq % Hkv == 0, (Hq, Hkv)
        return {
            "x": _w((lambda *s: torch.randn(*s, dtype=torch.bfloat16) * 0.05)(B, Sq, D)),
            "k_cache": _w((lambda *s: torch.randn(*s, dtype=torch.bfloat16) * 6.4)(B, Hkv, Sk, Dh)),
            "v_cache": _w((lambda *s: torch.randn(*s, dtype=torch.bfloat16) * 0.4)(B, Hkv, Sk, Dh)),
            "wq": _w((lambda *s: torch.randn(*s, dtype=torch.bfloat16) * 6.4)(D, Hq * Dh) * (D ** -0.5)),
            "wo": _w((lambda *s: torch.randn(*s, dtype=torch.bfloat16) * 0.4)(Hq * Dh, D) * ((Hq * Dh) ** -0.5)),
        }
    _A_in = _A_setup()

    def _B_setup():
        B, S, D, F = 8, 1, 448, 1792
        return {
            "x": _w((lambda *s: torch.randn(*s, dtype=torch.bfloat16) * 0.05)(B, S, D)),
            "w1": _w((lambda *s: torch.randn(*s, dtype=torch.bfloat16) * 0.8)(D, F) * (D ** -0.5)),
            "b1": _w((lambda *s: torch.randn(*s, dtype=torch.bfloat16) * 0.8)(F)),
            "w2": _w((lambda *s: torch.randn(*s, dtype=torch.bfloat16) * 0.05)(F, D) * (F ** -0.5)),
            "b2": _w((lambda *s: torch.randn(*s, dtype=torch.bfloat16) * 0.05)(D)),
        }
    _B_in = _B_setup()

    return {
        "A_x": _A_in["x"],
        "A_k_cache": _A_in["k_cache"],
        "A_v_cache": _A_in["v_cache"],
        "A_wq": _A_in["wq"],
        "A_wo": _A_in["wo"],
        "B_x": _B_in["x"],
        "B_w1": _B_in["w1"],
        "B_b1": _B_in["b1"],
        "B_w2": _B_in["w2"],
        "B_b2": _B_in["b2"],
        "gate_w": _w((lambda *s: torch.randn(*s, dtype=torch.bfloat16) * 0.05)(448) * 16.0),
    }

def reference(A_x, A_k_cache, A_v_cache, A_wq, A_wo, B_x, B_w1, B_b1, B_w2, B_b2, gate_w):
    def _A_ref(x, k_cache, v_cache, wq, wo):
        B, Sq, D = x.shape
        Hq, Dh = 16, 256
        Hkv, Sk = k_cache.shape[1], k_cache.shape[2]
        W = min(4096, max(256, Sk // 4))
        rep = Hq // Hkv
        q = (lambda x, *d: x.permute(*d))((x @ wq).reshape(B, Sq, Hq, Dh), 0, 2, 1, 3)
        k = (lambda x, n, axis: torch.repeat_interleave(x, n, dim=axis))(k_cache[:, :, Sk - W:, :], rep, axis=1)
        v = (lambda x, n, axis: torch.repeat_interleave(x, n, dim=axis))(v_cache[:, :, Sk - W:, :], rep, axis=1)
        scores = torch.einsum("bhqd,bhkd->bhqk", q, k) * (Dh ** -0.5)
        p = _softmax(scores, axis=-1)
        o = torch.einsum("bhqk,bhkd->bhqd", p, v)
        return (lambda x, *d: x.permute(*d))(o, 0, 2, 1, 3).reshape(B, Sq, Hq * Dh) @ wo

    def _B_ref(x, w1, b1, w2, b2):
        y = _layernorm(x, axis=-1)
        h = _gelu(torch.einsum("bsd,df->bsf", y, w1) + b1)
        return torch.einsum("bsf,fd->bsd", h, w2) + b2

    x = A_x
    g = _sigmoid((x * gate_w).sum(-1, keepdims=True))
    a = _A_ref(x, A_k_cache, A_v_cache, A_wq, A_wo)
    b = _B_ref(x, B_w1, B_b1, B_w2, B_b2)
    return g * a + (1 - g) * b
```

```cpp
#include <cuda_runtime.h>
#include <cuda_bf16.h>
#include <cuda.h>
#include <stdint.h>

namespace {

constexpr int NB = 8, DM = 448, SK = 4096, WIN = 1024, FF = 1792, QD = 4096;
constexpr int NCTA = 128, NPROJ = 112;
constexpr int NSTAGE = 12, STAGE_BYTES = 16384;
#define WINDOW 6
#define TAU 700
#define LEAD 2000
constexpr int NTHREADS = 288;

constexpr int OFF_SC = NSTAGE * STAGE_BYTES;
constexpr int OFF_PF = OFF_SC + 8192;
constexpr int OFF_RED = OFF_PF + 4096;
constexpr int OFF_Q = OFF_RED + 8192;
constexpr int OFF_MISC = OFF_Q + 1024;
constexpr int OFF_BAR = OFF_MISC + 256;
constexpr int SMEM_USED = OFF_BAR + 256;
constexpr int SMEM_BYTES = SMEM_USED + 1024;

constexpr unsigned SPIN_LIMIT = 1u << 22;

__device__ unsigned g_epoch[NCTA];
__device__ uint2 g_q[NB * 2048];
__device__ uint4 g_h[NPROJ * 32];
__device__ uint4 g_o[16 * 16 * 32];
__device__ uint4 g_part[7 * 16 * 128];

#define TLW(i, w)
#define TLMAX(i)

__device__ __forceinline__ uint32_t smem_u32(const void* p) { return (uint32_t)__cvta_generic_to_shared(p); }
__device__ __forceinline__ void mbar_init(uint32_t bar, int cnt) {
    asm volatile("mbarrier.init.shared::cta.b64 [%0], %1;" ::"r"(bar), "r"(cnt) : "memory");
}
__device__ __forceinline__ void mbar_expect_tx(uint32_t bar, uint32_t bytes) {
    asm volatile("mbarrier.arrive.expect_tx.shared::cta.b64 _, [%0], %1;" ::"r"(bar), "r"(bytes) : "memory");
}
__device__ __forceinline__ void mbar_arrive(uint32_t bar) {
    asm volatile("mbarrier.arrive.shared::cta.b64 _, [%0];" ::"r"(bar) : "memory");
}
__device__ __forceinline__ void mbar_arrive_n(uint32_t bar, uint32_t n) {
    asm volatile("mbarrier.arrive.shared::cta.b64 _, [%0], %1;" ::"r"(bar), "r"(n) : "memory");
}
__device__ __forceinline__ void st_async2(uint32_t addr, float a, float b, uint32_t bar) {
    asm volatile("st.async.weak.shared::cluster.mbarrier::complete_tx::bytes.v2.f32 [%0], {%1, %2}, [%3];"
                 ::"r"(addr), "f"(a), "f"(b), "r"(bar) : "memory");
}
__device__ __forceinline__ void mbar_wait(uint32_t bar, uint32_t parity) {
    uint32_t done;
    unsigned n = 0;
    do {
        asm volatile("{\n.reg .pred p;\nmbarrier.try_wait.parity.shared::cta.b64 p, [%1], %2;\nselp.u32 %0, 1, 0, p;\n}"
                     : "=r"(done) : "r"(bar), "r"(parity) : "memory");
        if (++n > SPIN_LIMIT) __trap();
    } while (!done);
}
__device__ __forceinline__ void tma2d(uint32_t dst, const CUtensorMap* tm, int c0, int c1, uint32_t bar, uint64_t pol) {
    asm volatile("cp.async.bulk.tensor.2d.shared::cluster.global.mbarrier::complete_tx::bytes.L2::cache_hint [%0], [%1, {%3, %4}], [%2], %5;"
                 ::"r"(dst), "l"(tm), "r"(bar), "r"(c0), "r"(c1), "l"(pol) : "memory");
}
__device__ __forceinline__ void tma3d(uint32_t dst, const CUtensorMap* tm, int c0, int c1, int c2, uint32_t bar, uint64_t pol) {
    asm volatile("cp.async.bulk.tensor.3d.shared::cluster.global.mbarrier::complete_tx::bytes.L2::cache_hint [%0], [%1, {%3, %4, %5}], [%2], %6;"
                 ::"r"(dst), "l"(tm), "r"(bar), "r"(c0), "r"(c1), "r"(c2), "l"(pol) : "memory");
}
__device__ __forceinline__ void ldsm4(uint32_t (&r)[4], uint32_t addr) {
    asm volatile("ldmatrix.sync.aligned.m8n8.x4.shared.b16 {%0,%1,%2,%3}, [%4];"
                 : "=r"(r[0]), "=r"(r[1]), "=r"(r[2]), "=r"(r[3]) : "r"(addr) : "memory");
}
__device__ __forceinline__ void ldsm4t(uint32_t (&r)[4], uint32_t addr) {
    asm volatile("ldmatrix.sync.aligned.m8n8.x4.trans.shared.b16 {%0,%1,%2,%3}, [%4];"
                 : "=r"(r[0]), "=r"(r[1]), "=r"(r[2]), "=r"(r[3]) : "r"(addr) : "memory");
}
__device__ __forceinline__ void mma16816(float (&c)[4], uint32_t a0, uint32_t a1, uint32_t a2, uint32_t a3, uint32_t b0, uint32_t b1) {
    asm volatile("mma.sync.aligned.m16n8k16.row.col.f32.bf16.bf16.f32 {%0,%1,%2,%3}, {%4,%5,%6,%7}, {%8,%9}, {%0,%1,%2,%3};"
                 : "+f"(c[0]), "+f"(c[1]), "+f"(c[2]), "+f"(c[3])
                 : "r"(a0), "r"(a1), "r"(a2), "r"(a3), "r"(b0), "r"(b1));
}
__device__ __forceinline__ void cons_sync() { asm volatile("bar.sync 1, 256;" ::: "memory"); }

__device__ __forceinline__ float bf16r(float v) { return __bfloat162float(__float2bfloat16_rn(v)); }
__device__ __forceinline__ uint32_t pack_bf16(float lo, float hi) {
    uint32_t r;
    asm("cvt.rn.bf16x2.f32 %0, %1, %2;" : "=r"(r) : "f"(hi), "f"(lo));
    return r;
}
__device__ __forceinline__ float bf_lo(uint32_t w) { return __uint_as_float(w << 16); }
__device__ __forceinline__ float bf_hi(uint32_t w) { return __uint_as_float(w & 0xffff0000u); }

__device__ __forceinline__ void st_pkt8(uint2* p, uint32_t d, uint32_t tag) {
    unsigned long long v = ((unsigned long long)tag << 32) | d;
    asm volatile("st.relaxed.gpu.global.b64 [%0], %1;" ::"l"(p), "l"(v) : "memory");
}
__device__ __forceinline__ uint32_t poll_pkt8(const uint2* p, uint32_t tag) {
    unsigned long long v;
    unsigned n = 0;
    do {
        asm volatile("ld.relaxed.gpu.global.b64 %0, [%1];" : "=l"(v) : "l"(p) : "memory");
        if (++n > SPIN_LIMIT) __trap();
    } while ((uint32_t)(v >> 32) != tag);
    return (uint32_t)v;
}
__device__ __forceinline__ void st_pkt16(uint4* p, uint32_t d0, uint32_t d1, uint32_t tag) {
    unsigned long long lo = ((unsigned long long)d1 << 32) | d0, hi = tag;
    asm volatile("{\n.reg .b128 t;\nmov.b128 t, {%1, %2};\nst.relaxed.gpu.global.b128 [%0], t;\n}" ::"l"(p), "l"(lo), "l"(hi) : "memory");
}
__device__ __forceinline__ void st_pkt16x(uint4* p, uint32_t d0, uint32_t d1, uint32_t d2, uint32_t d3) {
    unsigned long long lo = ((unsigned long long)d1 << 32) | d0, hi = ((unsigned long long)d3 << 32) | d2;
    asm volatile("{\n.reg .b128 t;\nmov.b128 t, {%1, %2};\nst.relaxed.gpu.global.b128 [%0], t;\n}" ::"l"(p), "l"(lo), "l"(hi) : "memory");
}
__device__ __forceinline__ void ld_pkt16(const uint4* p, unsigned long long& lo, unsigned long long& hi) {
    asm volatile("{\n.reg .b128 t;\nld.relaxed.gpu.global.b128 t, [%2];\nmov.b128 {%0, %1}, t;\n}" : "=l"(lo), "=l"(hi) : "l"(p) : "memory");
}
__device__ __forceinline__ void reld_pkt16(const uint4* p, unsigned long long& lo, unsigned long long& hi, bool need) {
    asm volatile("{\n.reg .b128 t;\n.reg .pred p;\nsetp.ne.u32 p, %3, 0;\nmov.b128 t, {%0, %1};\n@p ld.relaxed.gpu.global.b128 t, [%2];\nmov.b128 {%0, %1}, t;\n}"
                 : "+l"(lo), "+l"(hi) : "l"(p), "r"((uint32_t)need) : "memory");
}
__device__ __forceinline__ uint2 poll_pkt16(const uint4* p, uint32_t tag) {
    unsigned long long lo, hi;
    unsigned n = 0;
    do {
        ld_pkt16(p, lo, hi);
        if (++n > SPIN_LIMIT) __trap();
    } while ((uint32_t)hi != tag);
    return make_uint2((uint32_t)lo, (uint32_t)(lo >> 32));
}

__global__ void __cluster_dims__(2, 1, 1) __launch_bounds__(NTHREADS, 1)
fused_kernel(const __grid_constant__ CUtensorMap tmK, const __grid_constant__ CUtensorMap tmV,
             const __grid_constant__ CUtensorMap tmWo, const __grid_constant__ CUtensorMap tmW2,
             const __grid_constant__ CUtensorMap tmWq, const __grid_constant__ CUtensorMap tmW1,
             const __nv_bfloat16* __restrict__ x, const __nv_bfloat16* __restrict__ b1,
             const __nv_bfloat16* __restrict__ b2, const __nv_bfloat16* __restrict__ gate_w,
             __nv_bfloat16* __restrict__ out
             ) {
    extern __shared__ unsigned char smem_raw[];
    const uint32_t raw = smem_u32(smem_raw);
    const uint32_t sb = (raw + 1023u) & ~1023u;
    unsigned char* sp = smem_raw + (sb - raw);

    const int tid = threadIdx.x, warp = tid >> 5, lane = tid & 31;
    const int g = lane >> 2, t = lane & 3;
    const int j = blockIdx.x;
    const int hkv = j >> 4, bb = (j >> 1) & 7, s = j & 1;
    const bool proj = j < NPROJ;
    const int ph = j / 7, pc = j - ph * 7;

    const uint32_t bar_full = sb + OFF_BAR, bar_empty = bar_full + 8 * NSTAGE, bar_sc = bar_empty + 8 * NSTAGE;

    if (warp == 8) {
        if (lane == 0) {
            for (int i = 0; i < NSTAGE; i++) { mbar_init(bar_full + 8 * i, 1); mbar_init(bar_empty + 8 * i, 8); }
            mbar_init(bar_sc, 1);
            asm volatile("fence.mbarrier_init.release.cluster;" ::: "memory");
            asm volatile("fence.proxy.async.shared::cta;" ::: "memory");
        }
        __syncwarp();
        asm volatile("barrier.cluster.arrive.relaxed.aligned;" ::: "memory");
        if (lane == 0) {
            uint32_t t0;
            asm volatile("mov.u32 %0, %%globaltimer_lo;" : "=r"(t0));
            uint64_t pol;
            asm volatile("createpolicy.fractional.L2::evict_first.b64 %0, 1.0;" : "=l"(pol));
            const int row0 = (bb * 8 + hkv) * SK + (SK - WIN);
            mbar_expect_tx(bar_full, STAGE_BYTES);
            tma2d(sb, &tmWq, 32 * j, 0, bar_full, pol);
            mbar_expect_tx(bar_full + 8, STAGE_BYTES);
            tma2d(sb + STAGE_BYTES, &tmWq, 32 * j, 256, bar_full + 8, pol);
            mbar_expect_tx(bar_sc, 8192);
            const int ntiles = proj ? 38 : 35;
            int st = 2, par = 1, wst = 0, wpar = 0;
            for (int i = 2; i < ntiles; i++) {
                if (i >= WINDOW) {
                    mbar_wait(bar_full + 8 * wst, wpar);
                    if (++wst == NSTAGE) { wst = 0; wpar ^= 1; }
                }
                if (i >= NSTAGE) mbar_wait(bar_empty + 8 * st, par);
                if (TAU > 0 && i * TAU > LEAD) {
                    uint32_t now;
                    do { asm volatile("mov.u32 %0, %%globaltimer_lo;" : "=r"(now)); } while (now - t0 < (uint32_t)(i * TAU - LEAD));
                }
                const uint32_t dst = sb + st * STAGE_BYTES, bar = bar_full + 8 * st;
                if (i == 18) {
                    if (proj) {
                        mbar_expect_tx(bar, STAGE_BYTES);
                        tma2d(dst, &tmW1, 16 * j, 0, bar, pol);
                        tma2d(dst + 8192, &tmW1, 16 * j, 256, bar, pol);
                    } else {
                        mbar_arrive(bar);
                    }
                } else {
                    mbar_expect_tx(bar, i == 35 ? 112 * 128 : STAGE_BYTES);
                    if (i < 35) {
                        const bool isk = i < 18;
                        tma3d(dst, isk ? &tmK : &tmV, 0, isk ? row0 + s * 512 + (i - 2) * 32 : row0 + (i - 19) * 64, isk ? 0 : 2 * s, bar, pol);
                    } else {
                        tma2d(dst, i == 35 ? &tmW2 : &tmWo, pc * 64, i == 35 ? ph * 112 : ph * 256 + (i - 36) * 128, bar, pol);
                    }
                }
                if (++st == NSTAGE) { st = 0; par ^= 1; }
            }
        }
        __syncwarp();
        asm volatile("barrier.cluster.wait.acquire.aligned;" ::: "memory");
        return;
    }

    TLW(0, 0);
    uint2* q_slot = &g_q[(tid >> 4) * 2048 + 16 * j + (tid & 15)];
    if (tid < 128) st_pkt8(q_slot, 0u, 0u);
    uint32_t tag = *reinterpret_cast<volatile unsigned*>(&g_epoch[j]);
    uint32_t xb[8];
    {
        const uint32_t* xp = reinterpret_cast<const uint32_t*>(x + g * DM) + (warp < 7 ? warp : 0) * 32 + t;
#pragma unroll
        for (int i = 0; i < 8; i++) xb[i] = __ldg(xp + 4 * i);
    }
    uint32_t xw[7], gw[7];
#pragma unroll
    for (int i = 0; i < 7; i++) {
        xw[i] = __ldg(reinterpret_cast<const uint32_t*>(x + warp * DM) + lane + 32 * i);
        gw[i] = __ldg(reinterpret_cast<const uint32_t*>(gate_w) + lane + 32 * i);
    }
    const int fpos = lane & 7, fgrp = lane >> 3;
    const int fcol = pc * 64 + (ph >> 2) * 16 + 2 * (ph & 3) + (fpos >> 2) + 8 * (fgrp & 1);
    const int fb = 2 * (fpos & 3) + (fgrp >> 1);
    uint32_t b1w = 0;
    float b2v = 0.f;
    if (proj) {
        b1w = __ldg(reinterpret_cast<const uint32_t*>(b1 + 16 * j) + (tid & 7));
        b2v = __bfloat162float(b2[fcol]);
    }
    asm volatile("barrier.cluster.arrive.relaxed.aligned;" ::: "memory");
    asm volatile("barrier.cluster.wait.acquire.aligned;" ::: "memory");
    TLW(48, 0);
    float* misc = reinterpret_cast<float*>(sp + OFF_MISC);
    float* red = reinterpret_cast<float*>(sp + OFF_RED);
    const int r = lane & 7, mi = lane >> 3;
    if (warp < 7) {
        float c[2][4] = {};
        const int row = warp * 64 + r + 8 * (mi >> 1);
        const uint32_t qa0 = sb + row * 64 + (((mi & 1) ^ ((r >> 1) & 3)) << 4);
        const uint32_t qa1 = sb + row * 64 + (((2 + (mi & 1)) ^ ((r >> 1) & 3)) << 4);
        mbar_wait(bar_full + 8 * (warp >> 2), 0);
        TLW(61, 0);
#pragma unroll
        for (int ks = 0; ks < 4; ks++) {
            uint32_t a0[4], a1[4];
            ldsm4t(a0, qa0 + ks * 1024);
            ldsm4t(a1, qa1 + ks * 1024);
            mma16816(c[0], a0[0], a0[1], a0[2], a0[3], xb[2 * ks], xb[2 * ks + 1]);
            mma16816(c[1], a1[0], a1[1], a1[2], a1[3], xb[2 * ks], xb[2 * ks + 1]);
        }
        float* r0 = red + (warp * 8 + 2 * t) * 36 + g;
#pragma unroll
        for (int mt = 0; mt < 2; mt++) {
            r0[16 * mt] = c[mt][0];
            r0[36 + 16 * mt] = c[mt][1];
            r0[16 * mt + 8] = c[mt][2];
            r0[36 + 16 * mt + 8] = c[mt][3];
        }
    }
    TLMAX(53);
    cons_sync();
    tag = tag + 1u == 0u ? 1u : tag + 1u;
    if (tid < 128) {
        float v0 = 0.f, v1 = 0.f;
#pragma unroll
        for (int w = 0; w < 7; w++) {
            const float2 v = *reinterpret_cast<const float2*>(red + (w * 8 + (tid >> 4)) * 36 + 2 * (tid & 15));
            v0 += v.x; v1 += v.y;
        }
        st_pkt8(q_slot, pack_bf16(v0, v1), tag);
    } else if (tid >= 224 && tid < 226) {
        mbar_arrive_n(bar_empty + 8 * (tid - 224), 8);
    }
    TLW(1, 0);
    {
        float sum = 0.f, gs = 0.f;
#pragma unroll
        for (int i = 0; i < 7; i++) {
            sum += bf_lo(xw[i]) + bf_hi(xw[i]);
            gs += bf16r(bf_lo(xw[i]) * bf_lo(gw[i])) + bf16r(bf_hi(xw[i]) * bf_hi(gw[i]));
        }
#pragma unroll
        for (int o = 16; o; o >>= 1) { sum += __shfl_xor_sync(~0u, sum, o); gs += __shfl_xor_sync(~0u, gs, o); }
        const float mean = sum * (1.f / DM);
        float vs = 0.f;
#pragma unroll
        for (int i = 0; i < 7; i++) {
            const float d0 = bf_lo(xw[i]) - mean, d1 = bf_hi(xw[i]) - mean;
            vs += d0 * d0 + d1 * d1;
        }
#pragma unroll
        for (int o = 16; o; o >>= 1) vs += __shfl_xor_sync(~0u, vs, o);
        if (lane == 0) {
            const float gt = bf16r(__fdividef(1.f, 1.f + __expf(-bf16r(gs))));
            misc[warp] = gt;
            misc[8 + warp] = bf16r(1.f - gt);
            misc[32 + warp] = bf16r(mean);
            misc[40 + warp] = bf16r(__fsqrt_rn(bf16r(bf16r(vs * (1.f / DM)) + 1e-5f)));
        }
    }
    reinterpret_cast<uint32_t*>(sp + OFF_Q)[tid] = poll_pkt8(&g_q[bb * 2048 + hkv * 256 + tid], tag);
    TLW(55, 0); TLMAX(56);
    cons_sync();

    {
        uint32_t qa[16][2];
        const uint32_t* qs = reinterpret_cast<const uint32_t*>(sp + OFF_Q) + (g & 1) * 128 + t;
#pragma unroll
        for (int ks = 0; ks < 16; ks++) { qa[ks][0] = qs[ks * 8]; qa[ks][1] = qs[ks * 8 + 4]; }
        const uint32_t a_even = ((warp & 3) * 8 + r) * 128 + ((mi ^ r) << 4);
        const uint32_t a_odd = ((warp & 3) * 8 + r) * 128 + (((mi + 4) ^ r) << 4);
        const uint32_t sc_local = sb + OFF_SC + (g & 1) * 4096 + ((s * 16 + (warp >> 2)) * 4 + t) * 32 + (warp & 3) * 8;
        uint32_t sc_dst, bar_dst;
        asm("mapa.shared::cluster.u32 %0, %1, %2;" : "=r"(sc_dst) : "r"(sc_local), "r"((g >> 1) & 1));
        asm("mapa.shared::cluster.u32 %0, %1, %2;" : "=r"(bar_dst) : "r"(bar_sc), "r"((g >> 1) & 1));
        int st = 2 + (warp >> 2), par = 0;
        for (int i = 0; i < 8; i++) {
            mbar_wait(bar_full + 8 * st, par);
            TLW(8 + i, 0);
            const uint32_t base = sb + st * STAGE_BYTES;
            float ca[4] = {}, cb[4] = {}, cc[4] = {}, cd[4] = {};
#pragma unroll
            for (int c = 0; c < 4; c++) {
                uint32_t k0[4], k1[4];
                ldsm4(k0, base + c * 4096 + a_even);
                ldsm4(k1, base + c * 4096 + a_odd);
                mma16816(ca, qa[4 * c][0], qa[4 * c][0], qa[4 * c][1], qa[4 * c][1], k0[0], k0[1]);
                mma16816(cb, qa[4 * c + 1][0], qa[4 * c + 1][0], qa[4 * c + 1][1], qa[4 * c + 1][1], k0[2], k0[3]);
                mma16816(cc, qa[4 * c + 2][0], qa[4 * c + 2][0], qa[4 * c + 2][1], qa[4 * c + 2][1], k1[0], k1[1]);
                mma16816(cd, qa[4 * c + 3][0], qa[4 * c + 3][0], qa[4 * c + 3][1], qa[4 * c + 3][1], k1[2], k1[3]);
            }
            __syncwarp();
            if (lane == 0) mbar_arrive_n(bar_empty + 8 * st, 2);
            if (g < 4) {
                const float s0 = bf16r((ca[0] + cb[0]) + (cc[0] + cd[0])) * 0.0625f;
                const float s1 = bf16r((ca[1] + cb[1]) + (cc[1] + cd[1])) * 0.0625f;
                st_async2(sc_dst + i * 256, s0, s1, bar_dst);
            }
            st += 2;
            if (st >= NSTAGE) { st -= NSTAGE; par ^= 1; }
        }
    }
    TLW(58, 0);
    uint4* o_slot = &g_o[(((2 * hkv + (g & 1)) * 16 + s * 8 + warp) * 8 + bb) * 4 + (g >> 1)];
    uint4* part_slot = &g_part[(pc * 16 + ph) * 128 + (tid & 127)];
    if (t == 0) st_pkt16(o_slot, 0u, 0u, 0u);
    if (proj && tid < 128) st_pkt16x(part_slot, 0u, 0u, 0u, (tag + 128u) & 255u);
    int st = 18 % NSTAGE, par = (18 / NSTAGE) & 1;
    {
        mbar_wait(bar_full + 8 * st, par);
        if (proj) {
            if (warp < 7) {
                const float mb = misc[32 + g], sd = misc[40 + g];
                const uint32_t ha = sb + st * STAGE_BYTES + (warp * 64 + r + 8 * (mi >> 1)) * 32 + (((mi & 1) ^ (r >> 2)) << 4);
                float c[4] = {};
#pragma unroll
                for (int ks = 0; ks < 4; ks++) {
                    uint32_t a2[4], y[2];
                    ldsm4t(a2, ha + ks * 512);
#pragma unroll
                    for (int i = 0; i < 2; i++)
                        y[i] = pack_bf16(__fdividef(bf16r(bf_lo(xb[2 * ks + i]) - mb), sd), __fdividef(bf16r(bf_hi(xb[2 * ks + i]) - mb), sd));
                    mma16816(c, a2[0], a2[1], a2[2], a2[3], y[0], y[1]);
                }
                float* r0 = red + (warp * 8 + 2 * t) * 36 + g;
                r0[0] = c[0]; r0[36] = c[1]; r0[8] = c[2]; r0[44] = c[3];
            }
            cons_sync();
            if (tid < 64) {
                const int b = tid >> 3, cp = tid & 7;
                float v[2] = {0.f, 0.f};
#pragma unroll
                for (int w = 0; w < 7; w++) {
                    const float2 u = *reinterpret_cast<const float2*>(red + (w * 8 + b) * 36 + 2 * cp);
                    v[0] += u.x; v[1] += u.y;
                }
                v[0] = bf16r(bf16r(v[0]) + bf_lo(b1w));
                v[1] = bf16r(bf16r(v[1]) + bf_hi(b1w));
#pragma unroll
                for (int i = 0; i < 2; i++) {
                    const float u = v[i];
                    v[i] = u - __fdividef(u, __expf(fminf(1.5957691216057308f * (u + 0.044715f * u * u * u), 80.f)) + 1.f);
                }
                const uint32_t w0 = pack_bf16(v[0], v[1]);
                const uint32_t w1w = __shfl_down_sync(~0u, w0, 4);
                if (cp < 4) st_pkt16(&g_h[j * 32 + b * 4 + cp], w0, w1w, tag);
            }
        }
        if (tid == 224) mbar_arrive_n(bar_empty + 8 * st, 8);
        if (++st == NSTAGE) { st = 0; par ^= 1; }
    }
    TLW(60, 0);
    mbar_wait(bar_sc, 0);
    TLW(3, 0);
    {
        const float4* scp = reinterpret_cast<const float4*>(sp + OFF_SC) + tid * 2;
        const float4 u0 = scp[0], u1 = scp[1];
        float e[8] = {u0.x, u0.y, u0.z, u0.w, u1.x, u1.y, u1.z, u1.w};
        float m = e[0];
#pragma unroll
        for (int i = 1; i < 8; i++) m = fmaxf(m, e[i]);
#pragma unroll
        for (int o = 16; o; o >>= 1) m = fmaxf(m, __shfl_xor_sync(~0u, m, o));
        if (lane == 0) misc[16 + warp] = m;
        cons_sync();
        const float4 mm = *reinterpret_cast<const float4*>(misc + 16 + (warp & 4));
        m = fmaxf(fmaxf(mm.x, mm.y), fmaxf(mm.z, mm.w));
        float l = 0.f;
#pragma unroll
        for (int i = 0; i < 8; i++) { e[i] = __expf(e[i] - m); l += e[i]; }
#pragma unroll
        for (int o = 16; o; o >>= 1) l += __shfl_xor_sync(~0u, l, o);
        if (lane == 0) misc[24 + warp] = l;
        cons_sync();
        const float4 ll = *reinterpret_cast<const float4*>(misc + 24 + (warp & 4));
        const float inv = __fdividef(1.f, (ll.x + ll.y) + (ll.z + ll.w));
        reinterpret_cast<uint4*>(sp + OFF_PF)[tid] =
            make_uint4(pack_bf16(e[0] * inv, e[1] * inv), pack_bf16(e[2] * inv, e[3] * inv),
                       pack_bf16(e[4] * inv, e[5] * inv), pack_bf16(e[6] * inv, e[7] * inv));
        cons_sync();
    }
    const uint32_t trow = (r + 8 * (mi >> 1)) * 128;
    {
        float ca[4] = {}, cb[4] = {};
        const uint32_t va = (warp >> 2) * 8192 + trow + (((2 * (warp & 3) + (mi & 1)) ^ r) << 4);
        const uint4* pf = reinterpret_cast<const uint4*>(sp + OFF_PF) + (g & 1) * 128 + t;
        for (int i = 0; i < 16; i++) {
            const uint4 pw0 = pf[i * 8], pw1 = pf[i * 8 + 4];
            mbar_wait(bar_full + 8 * st, par);
            TLW(32 + i, 0);
            const uint32_t base = sb + st * STAGE_BYTES + va;
            uint32_t v0[4], v1[4], v2[4], v3[4];
            ldsm4t(v0, base);
            ldsm4t(v1, base + 2048);
            ldsm4t(v2, base + 4096);
            ldsm4t(v3, base + 6144);
            mma16816(ca, v0[0], v0[1], v0[2], v0[3], pw0.x, pw0.y);
            mma16816(cb, v1[0], v1[1], v1[2], v1[3], pw0.z, pw0.w);
            mma16816(ca, v2[0], v2[1], v2[2], v2[3], pw1.x, pw1.y);
            mma16816(cb, v3[0], v3[1], v3[2], v3[3], pw1.z, pw1.w);
            __syncwarp();
            if (lane == 0) mbar_arrive(bar_empty + 8 * st);
            if (++st == NSTAGE) { st = 0; par ^= 1; }
        }
#pragma unroll
        for (int i = 0; i < 4; i++) ca[i] += cb[i];
        const bool odd = g & 1;
        const float n0 = __shfl_xor_sync(~0u, odd ? ca[0] : ca[1], 4);
        const float n1 = __shfl_xor_sync(~0u, odd ? ca[2] : ca[3], 4);
        const uint32_t w0 = odd ? pack_bf16(n0, ca[1]) : pack_bf16(ca[0], n0);
        const uint32_t w1w = odd ? pack_bf16(n1, ca[3]) : pack_bf16(ca[2], n1);
        if (t == 0) st_pkt16(o_slot, w0, w1w, tag);
    }
    TLMAX(18);
    if (proj) {
        constexpr int S35 = 35 % NSTAGE, P35 = (35 / NSTAGE) & 1, S36 = 36 % NSTAGE, P36 = (36 / NSTAGE) & 1,
                      S37 = 37 % NSTAGE, P37 = (37 / NSTAGE) & 1;
        uint2* bfr = reinterpret_cast<uint2*>(sp + OFF_RED) + lane;
        if (warp >= 4) {
            const int w4 = warp - 4;
            const uint4* src[6];
#pragma unroll
            for (int i = 0; i < 4; i++) src[i] = &g_o[(ph * 16 + 4 * w4 + i) * 32 + lane];
            src[4] = &g_h[(ph * 7 + 2 * w4) * 32 + lane];
            src[5] = &g_h[(ph * 7 + (w4 < 3 ? 2 * w4 + 1 : 6)) * 32 + lane];
            unsigned long long lo[6], hi[6];
#pragma unroll
            for (int i = 0; i < 6; i++) ld_pkt16(src[i], lo[i], hi[i]);
            for (unsigned n = 0;; n++) {
                bool need[6], any = false;
#pragma unroll
                for (int i = 0; i < 6; i++) { need[i] = (uint32_t)hi[i] != tag; any |= need[i]; }
                if (!__any_sync(~0u, any)) break;
#pragma unroll
                for (int i = 0; i < 6; i++) reld_pkt16(src[i], lo[i], hi[i], need[i]);
                if (n > SPIN_LIMIT) __trap();
            }
#pragma unroll
            for (int i = 0; i < 6; i++)
                bfr[(i < 4 ? 4 * w4 + i : 16 + 2 * w4 + (i - 4)) * 32] = make_uint2((uint32_t)lo[i], (uint32_t)(lo[i] >> 32));
            __syncwarp();
            TLMAX(16);
            asm volatile("bar.arrive 2, 256;" ::: "memory");
            if (warp == 4) {
                const uint4* pp = &g_part[(pc * 16 + 4 * fgrp) * 128 + ph * 8 + fpos];
                const float om = misc[8 + fb];
                const uint32_t tg = tag & 255u;
                unsigned long long l[4], h[4];
#pragma unroll
                for (int i = 0; i < 4; i++) ld_pkt16(pp + i * 128, l[i], h[i]);
                for (unsigned n = 0;; n++) {
                    bool need[4], any = false;
#pragma unroll
                    for (int i = 0; i < 4; i++) { need[i] = ((uint32_t)(h[i] >> 32) & 255u) != tg; any |= need[i]; }
                    if (!__any_sync(~0u, any)) break;
#pragma unroll
                    for (int i = 0; i < 4; i++) reld_pkt16(pp + i * 128, l[i], h[i], need[i]);
                    if (n > SPIN_LIMIT) __trap();
                }
                __syncwarp();
                TLMAX(29);
                float f[4];
                f[0] = (__uint_as_float((uint32_t)l[0]) + __uint_as_float((uint32_t)l[1])) + (__uint_as_float((uint32_t)l[2]) + __uint_as_float((uint32_t)l[3]));
                f[1] = (__uint_as_float((uint32_t)(l[0] >> 32)) + __uint_as_float((uint32_t)(l[1] >> 32))) + (__uint_as_float((uint32_t)(l[2] >> 32)) + __uint_as_float((uint32_t)(l[3] >> 32)));
                f[2] = (__uint_as_float((uint32_t)h[0]) + __uint_as_float((uint32_t)h[1])) + (__uint_as_float((uint32_t)h[2]) + __uint_as_float((uint32_t)h[3]));
                f[3] = (__uint_as_float((uint32_t)(h[0] >> 32) & ~255u) + __uint_as_float((uint32_t)(h[1] >> 32) & ~255u)) +
                       (__uint_as_float((uint32_t)(h[2] >> 32) & ~255u) + __uint_as_float((uint32_t)(h[3] >> 32) & ~255u));
                const bool up = fgrp & 1;
                const float k0 = (up ? f[2] : f[0]) + __shfl_xor_sync(~0u, up ? f[0] : f[2], 8);
                const float k1 = (up ? f[3] : f[1]) + __shfl_xor_sync(~0u, up ? f[1] : f[3], 8);
                const bool up2 = fgrp >> 1;
                const float res = (up2 ? k1 : k0) + __shfl_xor_sync(~0u, up2 ? k0 : k1, 16);
                out[fb * DM + fcol] = __float2bfloat16_rn(res + om * b2v);
                TLMAX(30);
            }
        } else {
            const uint32_t ca = trow + (((2 * warp + (mi & 1)) ^ r) << 4);
            uint32_t a2[7][4], aa[8][4];
            mbar_wait(bar_full + 8 * S35, P35);
#pragma unroll
            for (int ks = 0; ks < 7; ks++) ldsm4t(a2[ks], sb + S35 * STAGE_BYTES + ks * 2048 + ca);
            mbar_wait(bar_full + 8 * S36, P36);
#pragma unroll
            for (int ks = 0; ks < 8; ks++) ldsm4t(aa[ks], sb + S36 * STAGE_BYTES + ks * 2048 + ca);
            const float g0 = misc[2 * t], g1 = misc[2 * t + 1], m0 = misc[8 + 2 * t], m1 = misc[8 + 2 * t + 1];
            TLMAX(24);
            asm volatile("bar.sync 2, 256;" ::: "memory");
            float acm[2][4] = {}, acc[4][4] = {};
            uint2 ob[8];
#pragma unroll
            for (int ks = 0; ks < 8; ks++) {
                const uint2 bv = bfr[ks * 32];
                mma16816(acc[ks & 3], aa[ks][0], aa[ks][1], aa[ks][2], aa[ks][3], bv.x, bv.y);
            }
#pragma unroll
            for (int ks = 0; ks < 8; ks++) ob[ks] = bfr[(8 + ks) * 32];
#pragma unroll
            for (int ks = 0; ks < 7; ks++) {
                const uint2 bv = bfr[(16 + ks) * 32];
                mma16816(acm[ks & 1], a2[ks][0], a2[ks][1], a2[ks][2], a2[ks][3], bv.x, bv.y);
            }
            mbar_wait(bar_full + 8 * S37, P37);
            TLMAX(17);
#pragma unroll
            for (int ks = 0; ks < 8; ks++) ldsm4t(aa[ks], sb + S37 * STAGE_BYTES + ks * 2048 + ca);
#pragma unroll
            for (int ks = 0; ks < 8; ks++) mma16816(acc[ks & 3], aa[ks][0], aa[ks][1], aa[ks][2], aa[ks][3], ob[ks].x, ob[ks].y);
            float v[4];
#pragma unroll
            for (int i = 0; i < 4; i++)
                v[i] = ((i & 1) ? g1 : g0) * ((acc[0][i] + acc[1][i]) + (acc[2][i] + acc[3][i])) + ((i & 1) ? m1 : m0) * (acm[0][i] + acm[1][i]);
            st_pkt16x(part_slot, __float_as_uint(v[0]), __float_as_uint(v[1]), __float_as_uint(v[2]),
                      (__float_as_uint(v[3]) & ~255u) | (tag & 255u));
            TLMAX(27);
        }
    }
    if (tid == 0) g_epoch[j] = tag;
}

typedef CUresult (*EncodeFn)(CUtensorMap*, CUtensorMapDataType, cuuint32_t, void*, const cuuint64_t*, const cuuint64_t*,
                             const cuuint32_t*, const cuuint32_t*, CUtensorMapInterleave, CUtensorMapSwizzle,
                             CUtensorMapL2promotion, CUtensorMapFloatOOBfill);

}

extern "C" void kernel_launch(void* const* d_in, const int* in_sizes, int n_in, void* d_out, int out_size) {
    (void)in_sizes; (void)n_in; (void)out_size;
    static EncodeFn encode = nullptr;
    if (!encode) {
        void* fn = nullptr;
        cudaDriverEntryPointQueryResult qr;
        cudaGetDriverEntryPoint("cuTensorMapEncodeTiled", &fn, cudaEnableDefault, &qr);
        encode = (EncodeFn)fn;
        cudaFuncSetAttribute(fused_kernel, cudaFuncAttributeMaxDynamicSharedMemorySize, SMEM_BYTES);
    }
    CUtensorMap tmK, tmV, tmWo, tmW2, tmWq, tmW1;
    const cuuint32_t es[3] = {1, 1, 1};
    {
        const cuuint64_t dims[3] = {64, (cuuint64_t)64 * SK, 4};
        const cuuint64_t strides[2] = {512, 128};
        const cuuint32_t boxK[3] = {64, 32, 4}, boxV[3] = {64, 64, 2};
        encode(&tmK, CU_TENSOR_MAP_DATA_TYPE_BFLOAT16, 3, d_in[1], dims, strides, boxK, es, CU_TENSOR_MAP_INTERLEAVE_NONE,
               CU_TENSOR_MAP_SWIZZLE_128B, CU_TENSOR_MAP_L2_PROMOTION_L2_256B, CU_TENSOR_MAP_FLOAT_OOB_FILL_NONE);
        encode(&tmV, CU_TENSOR_MAP_DATA_TYPE_BFLOAT16, 3, d_in[2], dims, strides, boxV, es, CU_TENSOR_MAP_INTERLEAVE_NONE,
               CU_TENSOR_MAP_SWIZZLE_128B, CU_TENSOR_MAP_L2_PROMOTION_L2_256B, CU_TENSOR_MAP_FLOAT_OOB_FILL_NONE);
    }
    {
        const cuuint64_t dimsO[2] = {DM, QD}, dims2[2] = {DM, FF};
        const cuuint64_t strides[1] = {DM * 2};
        const cuuint32_t boxO[2] = {64, 128}, box2[2] = {64, 112};
        encode(&tmWo, CU_TENSOR_MAP_DATA_TYPE_BFLOAT16, 2, d_in[4], dimsO, strides, boxO, es, CU_TENSOR_MAP_INTERLEAVE_NONE,
               CU_TENSOR_MAP_SWIZZLE_128B, CU_TENSOR_MAP_L2_PROMOTION_L2_128B, CU_TENSOR_MAP_FLOAT_OOB_FILL_NONE);
        encode(&tmW2, CU_TENSOR_MAP_DATA_TYPE_BFLOAT16, 2, d_in[8], dims2, strides, box2, es, CU_TENSOR_MAP_INTERLEAVE_NONE,
               CU_TENSOR_MAP_SWIZZLE_128B, CU_TENSOR_MAP_L2_PROMOTION_L2_128B, CU_TENSOR_MAP_FLOAT_OOB_FILL_NONE);
    }
    {
        const cuuint64_t dimsQ[2] = {QD, DM}, dims1[2] = {FF, DM};
        const cuuint64_t stridesQ[1] = {QD * 2}, strides1[1] = {FF * 2};
        const cuuint32_t boxQ[2] = {32, 256}, box1[2] = {16, 256};
        encode(&tmWq, CU_TENSOR_MAP_DATA_TYPE_BFLOAT16, 2, d_in[3], dimsQ, stridesQ, boxQ, es, CU_TENSOR_MAP_INTERLEAVE_NONE,
               CU_TENSOR_MAP_SWIZZLE_64B, CU_TENSOR_MAP_L2_PROMOTION_NONE, CU_TENSOR_MAP_FLOAT_OOB_FILL_NONE);
        encode(&tmW1, CU_TENSOR_MAP_DATA_TYPE_BFLOAT16, 2, d_in[6], dims1, strides1, box1, es, CU_TENSOR_MAP_INTERLEAVE_NONE,
               CU_TENSOR_MAP_SWIZZLE_32B, CU_TENSOR_MAP_L2_PROMOTION_NONE, CU_TENSOR_MAP_FLOAT_OOB_FILL_NONE);
    }
    fused_kernel<<<NCTA, NTHREADS, SMEM_BYTES>>>(
        tmK, tmV, tmWo, tmW2, tmWq, tmW1, (const __nv_bfloat16*)d_in[0], (const __nv_bfloat16*)d_in[7], (const __nv_bfloat16*)d_in[9], (const __nv_bfloat16*)d_in[10], (__nv_bfloat16*)d_out
        );
}
```

```cpp
#include <cuda_runtime.h>
#include <cuda_bf16.h>
#include <cuda.h>
#include <stdint.h>

namespace {

constexpr int NB = 8, DM = 448, SK = 4096, WIN = 1024, FF = 1792, QD = 4096;
constexpr int NCTA = 128, NPROJ = 112;
#define NST 12
constexpr int NSTAGE = NST, STAGE_BYTES = 16384;
#define WINDOW 6
#define TAU 670
#define WPROMO CU_TENSOR_MAP_L2_PROMOTION_NONE
#define LEAD 1700
constexpr int NTHREADS = 288;

constexpr int OFF_SC = NSTAGE * STAGE_BYTES;
constexpr int OFF_RED = OFF_SC + 9216;
constexpr int OFF_PF = OFF_RED;
constexpr int OFF_Q = OFF_RED + 8192;
constexpr int OFF_MISC = OFF_Q + 1024;
constexpr int OFF_BAR = OFF_MISC + 256;
constexpr int SMEM_USED = OFF_BAR + 256;
constexpr int SMEM_BYTES = SMEM_USED + 1024;

constexpr unsigned SPIN_LIMIT = 1u << 22;

struct Scratch {
    uint4 o[16 * 16 * 32];
    uint4 h[NPROJ * 32];
    uint2 q[NB * 2048];
    uint2 box[8 * NB * DM];
    unsigned long long acc[NB * DM];
    unsigned epoch[NCTA];
};
__device__ Scratch g_scratch;

struct Params {
    Scratch* sc;
    const __nv_bfloat16 *wq, *x, *gate_w, *b1, *b2;
    __nv_bfloat16* out;
    int tau, lead;
};

#define TLW(i, w)
#define TLMAX(i)

__device__ __forceinline__ uint32_t smem_u32(const void* p) { return (uint32_t)__cvta_generic_to_shared(p); }
__device__ __forceinline__ void mbar_init(uint32_t bar, int cnt) {
    asm volatile("mbarrier.init.shared::cta.b64 [%0], %1;" ::"r"(bar), "r"(cnt) : "memory");
}
__device__ __forceinline__ void mbar_expect_tx(uint32_t bar, uint32_t bytes) {
    asm volatile("mbarrier.arrive.expect_tx.shared::cta.b64 _, [%0], %1;" ::"r"(bar), "r"(bytes) : "memory");
}
__device__ __forceinline__ void mbar_arrive(uint32_t bar) {
    asm volatile("mbarrier.arrive.shared::cta.b64 _, [%0];" ::"r"(bar) : "memory");
}
__device__ __forceinline__ void mbar_arrive_n(uint32_t bar, uint32_t n) {
    asm volatile("mbarrier.arrive.shared::cta.b64 _, [%0], %1;" ::"r"(bar), "r"(n) : "memory");
}
__device__ __forceinline__ void st_async2(uint32_t addr, float a, float b, uint32_t bar) {
    asm volatile("st.async.weak.shared::cluster.mbarrier::complete_tx::bytes.v2.f32 [%0], {%1, %2}, [%3];"
                 ::"r"(addr), "f"(a), "f"(b), "r"(bar) : "memory");
}
__device__ __forceinline__ void mbar_wait(uint32_t bar, uint32_t parity) {
    uint32_t done;
    unsigned n = 0;
    do {
        asm volatile("{\n.reg .pred p;\nmbarrier.try_wait.parity.shared::cta.b64 p, [%1], %2;\nselp.u32 %0, 1, 0, p;\n}"
                     : "=r"(done) : "r"(bar), "r"(parity) : "memory");
        if (++n > SPIN_LIMIT) __trap();
    } while (!done);
}
__device__ __forceinline__ void tma2d(uint32_t dst, const CUtensorMap* tm, int c0, int c1, uint32_t bar, uint64_t pol) {
    asm volatile("cp.async.bulk.tensor.2d.shared::cluster.global.mbarrier::complete_tx::bytes.L2::cache_hint [%0], [%1, {%3, %4}], [%2], %5;"
                 ::"r"(dst), "l"(tm), "r"(bar), "r"(c0), "r"(c1), "l"(pol) : "memory");
}
__device__ __forceinline__ void tma3d(uint32_t dst, const CUtensorMap* tm, int c0, int c1, int c2, uint32_t bar, uint64_t pol) {
    asm volatile("cp.async.bulk.tensor.3d.shared::cluster.global.mbarrier::complete_tx::bytes.L2::cache_hint [%0], [%1, {%3, %4, %5}], [%2], %6;"
                 ::"r"(dst), "l"(tm), "r"(bar), "r"(c0), "r"(c1), "r"(c2), "l"(pol) : "memory");
}
__device__ __forceinline__ void ldsm4(uint32_t (&r)[4], uint32_t addr) {
    asm volatile("ldmatrix.sync.aligned.m8n8.x4.shared.b16 {%0,%1,%2,%3}, [%4];"
                 : "=r"(r[0]), "=r"(r[1]), "=r"(r[2]), "=r"(r[3]) : "r"(addr) : "memory");
}
__device__ __forceinline__ void ldsm4t(uint32_t (&r)[4], uint32_t addr) {
    asm volatile("ldmatrix.sync.aligned.m8n8.x4.trans.shared.b16 {%0,%1,%2,%3}, [%4];"
                 : "=r"(r[0]), "=r"(r[1]), "=r"(r[2]), "=r"(r[3]) : "r"(addr) : "memory");
}
__device__ __forceinline__ void mma16816(float (&c)[4], uint32_t a0, uint32_t a1, uint32_t a2, uint32_t a3, uint32_t b0, uint32_t b1) {
    asm volatile("mma.sync.aligned.m16n8k16.row.col.f32.bf16.bf16.f32 {%0,%1,%2,%3}, {%4,%5,%6,%7}, {%8,%9}, {%0,%1,%2,%3};"
                 : "+f"(c[0]), "+f"(c[1]), "+f"(c[2]), "+f"(c[3])
                 : "r"(a0), "r"(a1), "r"(a2), "r"(a3), "r"(b0), "r"(b1));
}
__device__ __forceinline__ void cons_sync() { asm volatile("bar.sync 1, 256;" ::: "memory"); }

__device__ __forceinline__ float bf16r(float v) { return __bfloat162float(__float2bfloat16_rn(v)); }
__device__ __forceinline__ uint32_t pack_bf16(float lo, float hi) {
    uint32_t r;
    asm("cvt.rn.bf16x2.f32 %0, %1, %2;" : "=r"(r) : "f"(hi), "f"(lo));
    return r;
}
__device__ __forceinline__ float bf_lo(uint32_t w) { return __uint_as_float(w << 16); }
__device__ __forceinline__ float bf_hi(uint32_t w) { return __uint_as_float(w & 0xffff0000u); }

__device__ __forceinline__ void st_pkt8(uint2* p, uint32_t d, uint32_t tag) {
    unsigned long long v = ((unsigned long long)tag << 32) | d;
    asm volatile("st.relaxed.gpu.global.b64 [%0], %1;" ::"l"(p), "l"(v) : "memory");
}
__device__ __forceinline__ uint32_t poll_pkt8(const uint2* p, uint32_t tag, unsigned slp) {
    unsigned long long v;
    for (unsigned n = 0;; n++) {
        asm volatile("ld.relaxed.gpu.global.b64 %0, [%1];" : "=l"(v) : "l"(p) : "memory");
        if ((uint32_t)(v >> 32) == tag) break;
        if (slp) __nanosleep(slp);
        if (n > SPIN_LIMIT) __trap();
    }
    return (uint32_t)v;
}
__device__ __forceinline__ void st_pkt16(uint4* p, uint32_t d0, uint32_t d1, uint32_t tag) {
    unsigned long long lo = ((unsigned long long)d1 << 32) | d0, hi = tag;
    asm volatile("{\n.reg .b128 t;\nmov.b128 t, {%1, %2};\nst.relaxed.gpu.global.b128 [%0], t;\n}" ::"l"(p), "l"(lo), "l"(hi) : "memory");
}
__device__ __forceinline__ void st_pkt16x(uint4* p, uint32_t d0, uint32_t d1, uint32_t d2, uint32_t d3) {
    unsigned long long lo = ((unsigned long long)d1 << 32) | d0, hi = ((unsigned long long)d3 << 32) | d2;
    asm volatile("{\n.reg .b128 t;\nmov.b128 t, {%1, %2};\nst.relaxed.gpu.global.b128 [%0], t;\n}" ::"l"(p), "l"(lo), "l"(hi) : "memory");
}
__device__ __forceinline__ void ld_pkt16(const uint4* p, unsigned long long& lo, unsigned long long& hi) {
    asm volatile("{\n.reg .b128 t;\nld.relaxed.gpu.global.b128 t, [%2];\nmov.b128 {%0, %1}, t;\n}" : "=l"(lo), "=l"(hi) : "l"(p) : "memory");
}
__device__ __forceinline__ void reld_pkt16(const uint4* p, unsigned long long& lo, unsigned long long& hi, bool need) {
    asm volatile("{\n.reg .b128 t;\n.reg .pred p;\nsetp.ne.u32 p, %3, 0;\nmov.b128 t, {%0, %1};\n@p ld.relaxed.gpu.global.b128 t, [%2];\nmov.b128 {%0, %1}, t;\n}"
                 : "+l"(lo), "+l"(hi) : "l"(p), "r"((uint32_t)need) : "memory");
}
__device__ __forceinline__ uint2 poll_pkt16(const uint4* p, uint32_t tag) {
    unsigned long long lo, hi;
    unsigned n = 0;
    do {
        ld_pkt16(p, lo, hi);
        if (++n > SPIN_LIMIT) __trap();
    } while ((uint32_t)hi != tag);
    return make_uint2((uint32_t)lo, (uint32_t)(lo >> 32));
}

__device__ __forceinline__ bool mbar_test(uint32_t bar, uint32_t parity) {
    uint32_t done;
    asm volatile("{\n.reg .pred p;\nmbarrier.test_wait.parity.shared::cta.b64 p, [%1], %2;\nselp.u32 %0, 1, 0, p;\n}"
                 : "=r"(done) : "r"(bar), "r"(parity) : "memory");
    return done;
}
__device__ __forceinline__ uint32_t pin(uint32_t v) { return __shfl_sync(~0u, v, threadIdx.x & 31); }
template <class T>
__device__ __forceinline__ T* pin(T* p) {
    return reinterpret_cast<T*>(__shfl_sync(~0u, reinterpret_cast<unsigned long long>(p), threadIdx.x & 31));
}
template <int N, int S>
__device__ __forceinline__ void gather_pkts(const uint4* p, uint32_t tag, unsigned long long (&lo)[N]) {
    unsigned long long hi[N];
#pragma unroll
    for (int i = 0; i < N; i++) ld_pkt16(p + 32 * (i & 1) + S * (i >> 1), lo[i], hi[i]);
    for (unsigned n = 0;; n++) {
        bool need[N], any = false;
#pragma unroll
        for (int i = 0; i < N; i++) { need[i] = (uint32_t)hi[i] != tag; any |= need[i]; }
        if (!__any_sync(~0u, any)) break;
#pragma unroll
        for (int i = 0; i < N; i++) reld_pkt16(p + 32 * (i & 1) + S * (i >> 1), lo[i], hi[i], need[i]);
        if (n > SPIN_LIMIT) __trap();
    }
}
__device__ __forceinline__ unsigned long long acc_encode(float v, int flags) {
    const float th = __fadd_rn(v, 12288.f);
    const float tl = __fadd_rn(__fsub_rn(v, __fsub_rn(th, 12288.f)), 0.0029296875f);
    const int hi = __float_as_int(th) - 0x46400000, lo = __float_as_int(tl) - 0x3b400000;
    return (unsigned long long)((long long)lo * 65536 + flags) + ((unsigned long long)(uint32_t)(hi << 6) << 32);
}
__device__ __forceinline__ float acc_decode(unsigned long long tot) {
    return fmaf((float)(int)(tot >> 32), 0x1p-16f, (float)((uint32_t)tot >> 16) * 0x1p-32f);
}

__global__ void __cluster_dims__(2, 1, 1) __launch_bounds__(NTHREADS, 1)
fused_kernel(const __grid_constant__ Params P, const __grid_constant__ CUtensorMap tmWq,
             const __grid_constant__ CUtensorMap tmK, const __grid_constant__ CUtensorMap tmV,
             const __grid_constant__ CUtensorMap tmW1, const __grid_constant__ CUtensorMap tmW2,
             const __grid_constant__ CUtensorMap tmWo) {
    extern __shared__ unsigned char smem_raw[];
    const uint32_t raw = smem_u32(smem_raw);
    const uint32_t sb = (raw + 1023u) & ~1023u;
    unsigned char* sp = smem_raw + (sb - raw);

    const int tid = threadIdx.x, warp = tid >> 5, lane = tid & 31;
    const int g = lane >> 2, t = lane & 3;
    const int j = blockIdx.x;
    const int hkv = j >> 4, bb = (j >> 1) & 7, s = j & 1;
    const bool proj = j < NPROJ;
    const int pk = j / 14, pc = j - pk * 14;

    const uint32_t bar_full = sb + OFF_BAR, bar_empty = bar_full + 8 * NSTAGE, bar_sc = bar_empty + 8 * NSTAGE;

    if (warp == 8) {
        TLW(20, 8);
        int tau = P.tau, lead = P.lead;
        uint64_t pol;
        asm volatile("createpolicy.fractional.L2::evict_first.b64 %0, 1.0;" : "=l"(pol));
        const int row0 = (bb * 8 + hkv) * SK + (SK - WIN);
        if (lane == 0) {
#pragma unroll
            for (int i = 0; i < 2; i++) mbar_init(bar_full + 8 * i, 1);
            asm volatile("fence.proxy.async.shared::cta;" ::: "memory");
            TLW(21, 8);
            mbar_expect_tx(bar_full, STAGE_BYTES);
            tma2d(sb, &tmWq, 32 * j, 0, bar_full, pol);
            TLW(22, 8);
            mbar_expect_tx(bar_full + 8, STAGE_BYTES);
            tma2d(sb + STAGE_BYTES, &tmWq, 32 * j, 256, bar_full + 8, pol);
            TLW(23, 8);
            asm volatile("prefetch.tensormap [%0];" ::"l"(&tmK) : "memory");
            asm volatile("prefetch.tensormap [%0];" ::"l"(&tmV) : "memory");
            asm volatile("prefetch.tensormap [%0];" ::"l"(&tmW1) : "memory");
            asm volatile("prefetch.tensormap [%0];" ::"l"(&tmW2) : "memory");
            asm volatile("prefetch.tensormap [%0];" ::"l"(&tmWo) : "memory");
#pragma unroll
            for (int i = 2; i < NSTAGE; i++) mbar_init(bar_full + 8 * i, 1);
#pragma unroll
            for (int i = 0; i < NSTAGE; i++) mbar_init(bar_empty + 8 * i, 8);
            mbar_init(bar_sc, 1);
            asm volatile("fence.mbarrier_init.release.cluster;" ::: "memory");
            asm volatile("fence.proxy.async.shared::cta;" ::: "memory");
        }
        __syncwarp();
        asm volatile("barrier.cluster.arrive.relaxed.aligned;" ::: "memory");
        if (lane == 0) {
            uint32_t t0;
            asm volatile("mov.u32 %0, %%globaltimer_lo;" : "=r"(t0));
            mbar_expect_tx(bar_sc, 8192);
            const int ntiles = proj ? 38 : 35;
            int st = 2, par = 1, wst = 0, wpar = 0, arrived = 0;
            for (int i = 2; i < ntiles; i++) {
                while (arrived <= i - WINDOW) {
                    mbar_wait(bar_full + 8 * wst, wpar);
                    if (++wst == NSTAGE) { wst = 0; wpar ^= 1; }
                    arrived++;
                }
                if (i >= NSTAGE) mbar_wait(bar_empty + 8 * st, par);
                {
                    const uint32_t due = max(i * tau - lead, 0);
                    uint32_t now;
                    do { asm volatile("mov.u32 %0, %%globaltimer_lo;" : "=r"(now)); } while (now - t0 < due);
                }
                const uint32_t dst = sb + st * STAGE_BYTES, bar = bar_full + 8 * st;
                if (i == 18) {
                    if (proj) {
                        mbar_expect_tx(bar, STAGE_BYTES);
                        tma2d(dst, &tmW1, 16 * j, 0, bar, pol);
                        tma2d(dst + 8192, &tmW1, 16 * j, 256, bar, pol);
                    } else {
                        mbar_arrive(bar);
                    }
                } else {
                    mbar_expect_tx(bar, i == 35 ? 224 * 64 : STAGE_BYTES);
                    if (i < 35) {
                        const bool isk = i < 18;
                        tma3d(dst, isk ? &tmK : &tmV, 0, isk ? row0 + s * 512 + (i - 2) * 32 : row0 + (i - 19) * 64, isk ? 0 : 2 * s, bar, pol);
                    } else {
                        tma2d(dst, i == 35 ? &tmW2 : &tmWo, pc * 32, i == 35 ? pk * 224 : pk * 512 + (i - 36) * 256, bar, pol);
                    }
                }
                if (i == 34) TLW(25, 8);
                if (i == 37) TLW(26, 8);
                if (++st == NSTAGE) { st = 0; par ^= 1; }
            }
        }
        __syncwarp();
        asm volatile("barrier.cluster.wait.acquire.aligned;" ::: "memory");
        return;
    }

    TLW(0, 0);
    Scratch* sc = P.sc;
    const __nv_bfloat16 *x = P.x, *gate_w = P.gate_w, *b1 = P.b1, *b2 = P.b2;
    __nv_bfloat16* out = P.out;
    if (tid == 224) asm volatile("st.shared.u32 [%0], %1;" ::"r"(sb + OFF_MISC + 252), "r"(P.tau) : "memory");
    if (lane == 0 && warp < 2)
        asm volatile("cp.async.bulk.prefetch.L2.global [%0], %1;"
                     ::"l"(reinterpret_cast<const char*>(P.wq) + (size_t)j * 28672 + warp * 14336), "r"(14336) : "memory");
    uint2* q_slot = &sc->q[(tid >> 4) * 2048 + 16 * j + (tid & 15)];
    if (tid < 128) st_pkt8(q_slot, 0u, 0u);
    uint32_t tag = *reinterpret_cast<volatile unsigned*>(&sc->epoch[j]);
    uint32_t xb[8];
    {
        const uint32_t* xp = reinterpret_cast<const uint32_t*>(x + g * DM) + (warp < 7 ? warp : 0) * 32 + t;
#pragma unroll
        for (int i = 0; i < 8; i++) xb[i] = __ldg(xp + 4 * i);
    }
    uint32_t xw[7], gw[7];
#pragma unroll
    for (int i = 0; i < 7; i++) {
        xw[i] = __ldg(reinterpret_cast<const uint32_t*>(x + warp * DM) + lane + 32 * i);
        gw[i] = __ldg(reinterpret_cast<const uint32_t*>(gate_w) + lane + 32 * i);
    }
    uint32_t b1w = 0;
    float b2v = 0.f;
    if (proj) {
        b1w = __ldg(reinterpret_cast<const uint32_t*>(b1 + 16 * j) + (tid & 7));
        b2v = __bfloat162float(b2[pc * 32 + lane]);
    }
    asm volatile("barrier.cluster.arrive.relaxed.aligned;" ::: "memory");
    asm volatile("barrier.cluster.wait.acquire.aligned;" ::: "memory");
    TLW(48, 0);
    float* misc = reinterpret_cast<float*>(sp + OFF_MISC);
    float* red = reinterpret_cast<float*>(sp + OFF_RED);
    const int r = lane & 7, mi = lane >> 3;
    if (warp < 7) {
        float c[2][4] = {};
        const int row = warp * 64 + r + 8 * (mi >> 1);
        const uint32_t qa0 = sb + row * 64 + (((mi & 1) ^ ((r >> 1) & 3)) << 4);
        const uint32_t qa1 = sb + row * 64 + (((2 + (mi & 1)) ^ ((r >> 1) & 3)) << 4);
        mbar_wait(bar_full + 8 * (warp >> 2), 0);
        TLW(61, 0);
#pragma unroll
        for (int ks = 0; ks < 4; ks++) {
            uint32_t a0[4], a1[4];
            ldsm4t(a0, qa0 + ks * 1024);
            ldsm4t(a1, qa1 + ks * 1024);
            mma16816(c[0], a0[0], a0[1], a0[2], a0[3], xb[2 * ks], xb[2 * ks + 1]);
            mma16816(c[1], a1[0], a1[1], a1[2], a1[3], xb[2 * ks], xb[2 * ks + 1]);
        }
        float* r0 = red + (warp * 8 + 2 * t) * 36 + g;
#pragma unroll
        for (int mt = 0; mt < 2; mt++) {
            r0[16 * mt] = c[mt][0];
            r0[36 + 16 * mt] = c[mt][1];
            r0[16 * mt + 8] = c[mt][2];
            r0[36 + 16 * mt + 8] = c[mt][3];
        }
    }
    TLMAX(53);
    cons_sync();
    tag = tag + 1u == 0u ? 1u : tag + 1u;
    if (tid < 128) {
        float v0 = 0.f, v1 = 0.f;
#pragma unroll
        for (int w = 0; w < 7; w++) {
            const float2 v = *reinterpret_cast<const float2*>(red + (w * 8 + (tid >> 4)) * 36 + 2 * (tid & 15));
            v0 += v.x; v1 += v.y;
        }
        st_pkt8(q_slot, pack_bf16(v0, v1), tag);
    } else if (tid >= 224 && tid < 226) {
        mbar_arrive_n(bar_empty + 8 * (tid - 224), 8);
    }
    TLW(1, 0);
    {
        float sum = 0.f, gs = 0.f;
#pragma unroll
        for (int i = 0; i < 7; i++) {
            sum += bf_lo(xw[i]) + bf_hi(xw[i]);
            gs += bf16r(bf_lo(xw[i]) * bf_lo(gw[i])) + bf16r(bf_hi(xw[i]) * bf_hi(gw[i]));
        }
#pragma unroll
        for (int o = 16; o; o >>= 1) { sum += __shfl_xor_sync(~0u, sum, o); gs += __shfl_xor_sync(~0u, gs, o); }
        const float mean = sum * (1.f / DM);
        float vs = 0.f;
#pragma unroll
        for (int i = 0; i < 7; i++) {
            const float d0 = bf_lo(xw[i]) - mean, d1 = bf_hi(xw[i]) - mean;
            vs += d0 * d0 + d1 * d1;
        }
#pragma unroll
        for (int o = 16; o; o >>= 1) vs += __shfl_xor_sync(~0u, vs, o);
        if (lane == 0) {
            const float gt = bf16r(__fdividef(1.f, 1.f + __expf(-bf16r(gs))));
            misc[warp] = gt;
            misc[8 + warp] = bf16r(1.f - gt);
            misc[32 + warp] = bf16r(mean);
            misc[40 + warp] = bf16r(__fsqrt_rn(bf16r(bf16r(vs * (1.f / DM)) + 1e-5f)));
        }
    }
    reinterpret_cast<uint32_t*>(sp + OFF_Q)[tid] = poll_pkt8(&sc->q[bb * 2048 + hkv * 256 + tid], tag, 0);
    TLW(55, 0); TLMAX(56);
    cons_sync();
    if (tid == 0) sc->epoch[j] = tag;

    {
        uint32_t qa[16][2];
        const uint32_t* qs = reinterpret_cast<const uint32_t*>(sp + OFF_Q) + (g & 1) * 128 + t;
#pragma unroll
        for (int ks = 0; ks < 16; ks++) { qa[ks][0] = qs[ks * 8]; qa[ks][1] = qs[ks * 8 + 4]; }
        const uint32_t a_even = ((warp & 3) * 8 + r) * 128 + ((mi ^ r) << 4);
        const uint32_t a_odd = ((warp & 3) * 8 + r) * 128 + (((mi + 4) ^ r) << 4);
        const uint32_t sc_local = sb + OFF_SC + (g & 1) * 4096 + ((s * 16 + (warp >> 2)) * 4 + t) * 32 + (warp & 3) * 8;
        uint32_t sc_dst, bar_dst;
        asm("mapa.shared::cluster.u32 %0, %1, %2;" : "=r"(sc_dst) : "r"(sc_local), "r"((g >> 1) & 1));
        asm("mapa.shared::cluster.u32 %0, %1, %2;" : "=r"(bar_dst) : "r"(bar_sc), "r"((g >> 1) & 1));
        int st = 2 + (warp >> 2), par = 0;
        for (int i = 0; i < 8; i++) {
            mbar_wait(bar_full + 8 * st, par);
            TLW(8 + i, 0);
            const uint32_t base = sb + st * STAGE_BYTES;
            float ca[4] = {}, cb[4] = {}, cc[4] = {}, cd[4] = {};
#pragma unroll
            for (int c = 0; c < 4; c++) {
                uint32_t k0[4], k1[4];
                ldsm4(k0, base + c * 4096 + a_even);
                ldsm4(k1, base + c * 4096 + a_odd);
                mma16816(ca, qa[4 * c][0], qa[4 * c][0], qa[4 * c][1], qa[4 * c][1], k0[0], k0[1]);
                mma16816(cb, qa[4 * c + 1][0], qa[4 * c + 1][0], qa[4 * c + 1][1], qa[4 * c + 1][1], k0[2], k0[3]);
                mma16816(cc, qa[4 * c + 2][0], qa[4 * c + 2][0], qa[4 * c + 2][1], qa[4 * c + 2][1], k1[0], k1[1]);
                mma16816(cd, qa[4 * c + 3][0], qa[4 * c + 3][0], qa[4 * c + 3][1], qa[4 * c + 3][1], k1[2], k1[3]);
            }
            __syncwarp();
            if (lane == 0) mbar_arrive_n(bar_empty + 8 * st, 2);
            if (g < 4) {
                const float s0 = bf16r((ca[0] + cb[0]) + (cc[0] + cd[0])) * 0.0625f;
                const float s1 = bf16r((ca[1] + cb[1]) + (cc[1] + cd[1])) * 0.0625f;
                st_async2(sc_dst + i * 256, s0, s1, bar_dst);
            }
            st += 2;
            if (st >= NSTAGE) { st -= NSTAGE; par ^= 1; }
        }
    }
    TLW(58, 0);
    uint4* o_slot = &sc->o[(((2 * hkv + (g & 1)) * 16 + s * 8 + warp) * 8 + bb) * 4 + (g >> 1)];
    if (t == 0) st_pkt16(o_slot, 0u, 0u, 0u);
    if (proj && warp == 4) {
        const float bv = misc[8 + pk] * b2v;
        const bool fits = fabsf(bv) < 2048.f;
        asm volatile("red.relaxed.gpu.global.add.u64 [%0], %1;"
                     ::"l"(&sc->acc[pk * DM + pc * 32 + lane]), "l"(acc_encode(fits ? bv : 0.f, fits ? 1 : 257)) : "memory");
    }
    int st = 18 % NSTAGE, par = (18 / NSTAGE) & 1;
    {
        mbar_wait(bar_full + 8 * st, par);
        if (proj) {
            if (warp < 7) {
                const float mb = misc[32 + g], sd = misc[40 + g];
                const uint32_t ha = sb + st * STAGE_BYTES + (warp * 64 + r + 8 * (mi >> 1)) * 32 + (((mi & 1) ^ (r >> 2)) << 4);
                float c[4] = {};
#pragma unroll
                for (int ks = 0; ks < 4; ks++) {
                    uint32_t a2[4], y[2];
                    ldsm4t(a2, ha + ks * 512);
#pragma unroll
                    for (int i = 0; i < 2; i++)
                        y[i] = pack_bf16(__fdividef(bf16r(bf_lo(xb[2 * ks + i]) - mb), sd), __fdividef(bf16r(bf_hi(xb[2 * ks + i]) - mb), sd));
                    mma16816(c, a2[0], a2[1], a2[2], a2[3], y[0], y[1]);
                }
                float* r0 = red + (warp * 8 + 2 * t) * 36 + g;
                r0[0] = c[0]; r0[36] = c[1]; r0[8] = c[2]; r0[44] = c[3];
            }
            cons_sync();
            if (tid < 64) {
                const int b = tid >> 3, cp = tid & 7;
                float v[2] = {0.f, 0.f};
#pragma unroll
                for (int w = 0; w < 7; w++) {
                    const float2 u = *reinterpret_cast<const float2*>(red + (w * 8 + b) * 36 + 2 * cp);
                    v[0] += u.x; v[1] += u.y;
                }
                v[0] = bf16r(bf16r(v[0]) + bf_lo(b1w));
                v[1] = bf16r(bf16r(v[1]) + bf_hi(b1w));
#pragma unroll
                for (int i = 0; i < 2; i++) {
                    const float u = v[i];
                    v[i] = u - __fdividef(u, __expf(fminf(1.5957691216057308f * (u + 0.044715f * u * u * u), 80.f)) + 1.f);
                }
                const uint32_t w0 = pack_bf16(v[0], v[1]);
                const uint32_t w1w = __shfl_down_sync(~0u, w0, 4);
                if (cp < 4) st_pkt16(&sc->h[j * 32 + b * 4 + cp], w0, w1w, tag);
            }
        }
        if (tid == 224) mbar_arrive_n(bar_empty + 8 * st, 8);
        if (++st == NSTAGE) { st = 0; par ^= 1; }
    }
    TLW(60, 0);
    mbar_wait(bar_sc, 0);
    TLW(3, 0);
    {
        const float4* scp = reinterpret_cast<const float4*>(sp + OFF_SC) + tid * 2;
        const float4 u0 = scp[0], u1 = scp[1];
        float e[8] = {u0.x, u0.y, u0.z, u0.w, u1.x, u1.y, u1.z, u1.w};
        float m = e[0];
#pragma unroll
        for (int i = 1; i < 8; i++) m = fmaxf(m, e[i]);
#pragma unroll
        for (int o = 16; o; o >>= 1) m = fmaxf(m, __shfl_xor_sync(~0u, m, o));
        if (lane == 0) misc[16 + warp] = m;
        cons_sync();
        const float4 mm = *reinterpret_cast<const float4*>(misc + 16 + (warp & 4));
        m = fmaxf(fmaxf(mm.x, mm.y), fmaxf(mm.z, mm.w));
        float l = 0.f;
#pragma unroll
        for (int i = 0; i < 8; i++) { e[i] = __expf(e[i] - m); l += e[i]; }
#pragma unroll
        for (int o = 16; o; o >>= 1) l += __shfl_xor_sync(~0u, l, o);
        if (lane == 0) misc[24 + warp] = l;
        cons_sync();
        const float4 ll = *reinterpret_cast<const float4*>(misc + 24 + (warp & 4));
        const float inv = __fdividef(1.f, (ll.x + ll.y) + (ll.z + ll.w));
        reinterpret_cast<uint4*>(sp + OFF_PF)[tid] =
            make_uint4(pack_bf16(e[0] * inv, e[1] * inv), pack_bf16(e[2] * inv, e[3] * inv),
                       pack_bf16(e[4] * inv, e[5] * inv), pack_bf16(e[6] * inv, e[7] * inv));
        cons_sync();
    }
    const uint32_t trow = (r + 8 * (mi >> 1)) * 128;
    {
        float ca[4] = {}, cb[4] = {};
        const uint32_t va = (warp >> 2) * 8192 + trow + (((2 * (warp & 3) + (mi & 1)) ^ r) << 4);
        const uint4* pf = reinterpret_cast<const uint4*>(sp + OFF_PF) + (g & 1) * 128 + t;
        for (int i = 0; i < 16; i++) {
            const uint4 pw0 = pf[i * 8], pw1 = pf[i * 8 + 4];
            mbar_wait(bar_full + 8 * st, par);
            TLW(32 + i, 0);
            const uint32_t base = sb + st * STAGE_BYTES + va;
            uint32_t v0[4], v1[4], v2[4], v3[4];
            ldsm4t(v0, base);
            ldsm4t(v1, base + 2048);
            ldsm4t(v2, base + 4096);
            ldsm4t(v3, base + 6144);
            mma16816(ca, v0[0], v0[1], v0[2], v0[3], pw0.x, pw0.y);
            mma16816(cb, v1[0], v1[1], v1[2], v1[3], pw0.z, pw0.w);
            mma16816(ca, v2[0], v2[1], v2[2], v2[3], pw1.x, pw1.y);
            mma16816(cb, v3[0], v3[1], v3[2], v3[3], pw1.z, pw1.w);
            __syncwarp();
            if (lane == 0) mbar_arrive(bar_empty + 8 * st);
            if (++st == NSTAGE) { st = 0; par ^= 1; }
        }
#pragma unroll
        for (int i = 0; i < 4; i++) ca[i] += cb[i];
        const bool odd = g & 1;
        const float n0 = __shfl_xor_sync(~0u, odd ? ca[0] : ca[1], 4);
        const float n1 = __shfl_xor_sync(~0u, odd ? ca[2] : ca[3], 4);
        const uint32_t w0 = odd ? pack_bf16(n0, ca[1]) : pack_bf16(ca[0], n0);
        const uint32_t w1w = odd ? pack_bf16(n1, ca[3]) : pack_bf16(ca[2], n1);
        if (t == 0) st_pkt16(o_slot, w0, w1w, tag);
    }
    TLMAX(18);
    if (proj) {
        constexpr int S35 = 35 % NSTAGE, P35 = (35 / NSTAGE) & 1, S36 = 36 % NSTAGE, P36 = (36 / NSTAGE) & 1,
                      S37 = 37 % NSTAGE, P37 = (37 / NSTAGE) & 1;
        const uint32_t wa0 = pin(sb + (warp * 32 + r + 8 * (mi >> 1)) * 64 + (((mi & 1) ^ ((r >> 1) & 3)) << 4));
        const uint32_t wa1 = wa0 ^ 32u;
        const int e = warp * DM + pc * 32 + lane;
        unsigned long long* accp = pin(&sc->acc[e]);
        __nv_bfloat16* outp = pin(out + e);
        const uint32_t rw = pin(sb + OFF_SC + ((warp * 8 + 2 * t) * 36 + g) * 4), rr = pin(sb + OFF_SC + (warp * 36 + lane) * 4);
        const uint4* op = pin(&sc->o[(pk * 32 + 2 * warp) * 32 + lane]);
        float acm[2][4] = {}, acc[2][2][4] = {};
        const float g0 = misc[2 * t], g1 = misc[2 * t + 1], m0 = misc[8 + 2 * t], m1 = misc[8 + 2 * t + 1];
        uint32_t aa[8][4];
        if (warp < 7) {
            unsigned long long hv[2];
            gather_pkts<2, 0>(&sc->h[(pk * 14 + 2 * warp) * 32 + lane], tag, hv);
            mbar_wait(bar_full + 8 * S35, P35);
#pragma unroll
            for (int ks = 0; ks < 2; ks++) {
                ldsm4t(aa[0], wa0 + S35 * STAGE_BYTES + ks * 1024);
                ldsm4t(aa[1], wa1 + S35 * STAGE_BYTES + ks * 1024);
                mma16816(acm[0], aa[0][0], aa[0][1], aa[0][2], aa[0][3], (uint32_t)hv[ks], (uint32_t)(hv[ks] >> 32));
                mma16816(acm[1], aa[1][0], aa[1][1], aa[1][2], aa[1][3], (uint32_t)hv[ks], (uint32_t)(hv[ks] >> 32));
            }
        } else {
            mbar_wait(bar_full + 8 * S35, P35);
        }
        unsigned long long ov[4], oh[4];
#pragma unroll
        for (int i = 0; i < 4; i++) ld_pkt16(op + 32 * (i & 1) + 512 * (i >> 1), ov[i], oh[i]);
        int have = 0;
        for (unsigned n = 0;; n++) {
            if (have == 0 && __all_sync(~0u, mbar_test(bar_full + 8 * S36, P36))) {
                have = 1;
#pragma unroll
                for (int i = 0; i < 4; i++) ldsm4t(aa[i], ((i & 1) ? wa1 : wa0) + S36 * STAGE_BYTES + (i >> 1) * 1024);
            }
            if (have == 1 && __all_sync(~0u, mbar_test(bar_full + 8 * S37, P37))) {
                have = 2;
#pragma unroll
                for (int i = 0; i < 4; i++) ldsm4t(aa[4 + i], ((i & 1) ? wa1 : wa0) + S37 * STAGE_BYTES + (i >> 1) * 1024);
            }
            bool need[4], any = false;
#pragma unroll
            for (int i = 0; i < 4; i++) { need[i] = (uint32_t)oh[i] != tag; any |= need[i]; }
            if (!__any_sync(~0u, any)) break;
#pragma unroll
            for (int i = 0; i < 4; i++) reld_pkt16(op + 32 * (i & 1) + 512 * (i >> 1), ov[i], oh[i], need[i]);
            if (n > SPIN_LIMIT) __trap();
        }
        TLMAX(16);
        if (have == 0) {
            mbar_wait(bar_full + 8 * S36, P36);
#pragma unroll
            for (int i = 0; i < 4; i++) ldsm4t(aa[i], ((i & 1) ? wa1 : wa0) + S36 * STAGE_BYTES + (i >> 1) * 1024);
        }
#pragma unroll
        for (int i = 0; i < 4; i++)
            mma16816(acc[i & 1][(i >> 1) & 1], aa[i][0], aa[i][1], aa[i][2], aa[i][3], (uint32_t)ov[i >> 1], (uint32_t)(ov[i >> 1] >> 32));
        if (have < 2) {
            mbar_wait(bar_full + 8 * S37, P37);
#pragma unroll
            for (int i = 0; i < 4; i++) ldsm4t(aa[4 + i], ((i & 1) ? wa1 : wa0) + S37 * STAGE_BYTES + (i >> 1) * 1024);
        }
        TLMAX(17);
#pragma unroll
        for (int i = 4; i < 8; i++)
            mma16816(acc[i & 1][(i >> 1) & 1], aa[i][0], aa[i][1], aa[i][2], aa[i][3], (uint32_t)ov[i >> 1], (uint32_t)(ov[i >> 1] >> 32));
#pragma unroll
        for (int mt = 0; mt < 2; mt++)
#pragma unroll
            for (int i = 0; i < 4; i++)
                asm volatile("st.shared.f32 [%0], %1;" ::"r"(rw + (16 * mt + 36 * (i & 1) + 8 * (i >> 1)) * 4),
                             "f"(((i & 1) ? g1 : g0) * (acc[mt][0][i] + acc[mt][1][i]) + ((i & 1) ? m1 : m0) * acm[mt][i]) : "memory");
        cons_sync();
        float u[8];
#pragma unroll
        for (int w = 0; w < 8; w++) asm volatile("ld.shared.f32 %0, [%1];" : "=f"(u[w]) : "r"(rr + w * 8 * 36 * 4) : "memory");
        const float v = ((u[0] + u[1]) + (u[2] + u[3])) + ((u[4] + u[5]) + (u[6] + u[7]));
        const uint32_t vmax = __reduce_max_sync(~0u, __float_as_uint(v) & 0x7fffffffu);
        unsigned long long add = acc_encode(v, 1);
        const bool boxed = vmax - 0x37800000u >= 0x45000000u - 0x37800000u;
        asm("{\n.reg .pred p;\nsetp.ne.u32 p, %1, 0;\n@p mov.b64 %0, 17;\n}" : "+l"(add) : "r"((uint32_t)boxed));
        unsigned long long tot;
        asm volatile("atom.relaxed.gpu.global.add.u64 %0, [%1], %2;" : "=l"(tot) : "l"(accp), "l"(add) : "memory");
        TLMAX(27);
        if (boxed) st_pkt8(&sc->box[pk * NB * DM + e], __float_as_uint(v), tag);
        tot += add;
        if (((uint32_t)tot & 15u) == 9u) {
            float res = acc_decode(tot);
            if ((uint32_t)tot & 0x1f0u) {
                const uint32_t nbox = ((uint32_t)tot >> 4) & 15u;
                if (nbox == 8u) res = 0.f;
                if (nbox == 8u || ((uint32_t)tot & 256u)) res += misc[8 + warp] * b2v;
                for (unsigned n = 0;; n++) {
                    float sum = 0.f;
                    uint32_t found = 0;
                    for (int k = 0; k < 8; k++) {
                        unsigned long long pv;
                        asm volatile("ld.relaxed.gpu.global.b64 %0, [%1];" : "=l"(pv) : "l"(&sc->box[k * NB * DM + e]) : "memory");
                        if ((uint32_t)(pv >> 32) == tag) { sum += __uint_as_float((uint32_t)pv); found++; }
                    }
                    if (found == nbox) { res += sum; break; }
                    if (n > SPIN_LIMIT) __trap();
                }
            }
            asm volatile("st.global.u16 [%0], %1;" ::"l"(outp), "h"(__bfloat16_as_ushort(__float2bfloat16_rn(res))) : "memory");
            asm volatile("st.global.u64 [%0], 0;" ::"l"(accp) : "memory");
        }
        TLMAX(30);
    }
}

typedef CUresult (*EncodeFn)(CUtensorMap*, CUtensorMapDataType, cuuint32_t, void*, const cuuint64_t*, const cuuint64_t*,
                             const cuuint32_t*, const cuuint32_t*, CUtensorMapInterleave, CUtensorMapSwizzle,
                             CUtensorMapL2promotion, CUtensorMapFloatOOBfill);

}

extern "C" void kernel_launch(void* const* d_in, const int* in_sizes, int n_in, void* d_out, int out_size) {
    (void)in_sizes; (void)n_in; (void)out_size;
    static EncodeFn encode = nullptr;
    static Scratch* scratch = nullptr;
    if (!encode) {
        cudaGetSymbolAddress((void**)&scratch, g_scratch);
        void* fn = nullptr;
        cudaDriverEntryPointQueryResult qr;
        cudaGetDriverEntryPoint("cuTensorMapEncodeTiled", &fn, cudaEnableDefault, &qr);
        encode = (EncodeFn)fn;
        cudaFuncSetAttribute(fused_kernel, cudaFuncAttributeMaxDynamicSharedMemorySize, SMEM_BYTES);
    }
    CUtensorMap tmK, tmV, tmWo, tmW2, tmWq, tmW1;
    const cuuint32_t es[3] = {1, 1, 1};
    {
        const cuuint64_t dims[3] = {64, (cuuint64_t)64 * SK, 4};
        const cuuint64_t strides[2] = {512, 128};
        const cuuint32_t boxK[3] = {64, 32, 4}, boxV[3] = {64, 64, 2};
        encode(&tmK, CU_TENSOR_MAP_DATA_TYPE_BFLOAT16, 3, d_in[1], dims, strides, boxK, es, CU_TENSOR_MAP_INTERLEAVE_NONE,
               CU_TENSOR_MAP_SWIZZLE_128B, CU_TENSOR_MAP_L2_PROMOTION_L2_256B, CU_TENSOR_MAP_FLOAT_OOB_FILL_NONE);
        encode(&tmV, CU_TENSOR_MAP_DATA_TYPE_BFLOAT16, 3, d_in[2], dims, strides, boxV, es, CU_TENSOR_MAP_INTERLEAVE_NONE,
               CU_TENSOR_MAP_SWIZZLE_128B, CU_TENSOR_MAP_L2_PROMOTION_L2_256B, CU_TENSOR_MAP_FLOAT_OOB_FILL_NONE);
    }
    {
        const cuuint64_t dimsO[2] = {DM, QD}, dims2[2] = {DM, FF};
        const cuuint64_t strides[1] = {DM * 2};
        const cuuint32_t boxO[2] = {32, 256}, box2[2] = {32, 224};
        encode(&tmWo, CU_TENSOR_MAP_DATA_TYPE_BFLOAT16, 2, d_in[4], dimsO, strides, boxO, es, CU_TENSOR_MAP_INTERLEAVE_NONE,
               CU_TENSOR_MAP_SWIZZLE_64B, WPROMO, CU_TENSOR_MAP_FLOAT_OOB_FILL_NONE);
        encode(&tmW2, CU_TENSOR_MAP_DATA_TYPE_BFLOAT16, 2, d_in[8], dims2, strides, box2, es, CU_TENSOR_MAP_INTERLEAVE_NONE,
               CU_TENSOR_MAP_SWIZZLE_64B, WPROMO, CU_TENSOR_MAP_FLOAT_OOB_FILL_NONE);
    }
    {
        const cuuint64_t dimsQ[2] = {QD, DM}, dims1[2] = {FF, DM};
        const cuuint64_t stridesQ[1] = {QD * 2}, strides1[1] = {FF * 2};
        const cuuint32_t boxQ[2] = {32, 256}, box1[2] = {16, 256};
        encode(&tmWq, CU_TENSOR_MAP_DATA_TYPE_BFLOAT16, 2, d_in[3], dimsQ, stridesQ, boxQ, es, CU_TENSOR_MAP_INTERLEAVE_NONE,
               CU_TENSOR_MAP_SWIZZLE_64B, CU_TENSOR_MAP_L2_PROMOTION_NONE, CU_TENSOR_MAP_FLOAT_OOB_FILL_NONE);
        encode(&tmW1, CU_TENSOR_MAP_DATA_TYPE_BFLOAT16, 2, d_in[6], dims1, strides1, box1, es, CU_TENSOR_MAP_INTERLEAVE_NONE,
               CU_TENSOR_MAP_SWIZZLE_32B, CU_TENSOR_MAP_L2_PROMOTION_NONE, CU_TENSOR_MAP_FLOAT_OOB_FILL_NONE);
    }
    Params P;
    P.sc = scratch;
    P.wq = (const __nv_bfloat16*)d_in[3]; P.x = (const __nv_bfloat16*)d_in[0]; P.gate_w = (const __nv_bfloat16*)d_in[10];
    P.b1 = (const __nv_bfloat16*)d_in[7]; P.b2 = (const __nv_bfloat16*)d_in[9]; P.out = (__nv_bfloat16*)d_out;
    P.tau = TAU; P.lead = LEAD;
    fused_kernel<<<NCTA, NTHREADS, SMEM_BYTES>>>(P, tmWq, tmK, tmV, tmW1, tmW2, tmWo);
}
```

```cpp
#include <cuda_runtime.h>
#include <cuda_bf16.h>
#include <cuda.h>
#include <stdint.h>

namespace {

constexpr int NB = 8, DM = 448, SK = 4096, WIN = 1024, FF = 1792, QD = 4096;
constexpr int NCTA = 128, NPROJ = 112;
#define NST 12
constexpr int NSTAGE = NST, STAGE_BYTES = 16384;
#define WINDOW 6
#define NEARLY 3
#define MTILE 23
#define RTILE 28
#define HPOS 11
constexpr double PACE_FRAC = 0.9255;
constexpr double PACE_LEAD = 2.78;
constexpr double PACE_BACKLOG = 3.32;
constexpr int PACE_GAIN16 = 21;
constexpr double PACE_GATE = 38.03;
constexpr int NTHREADS = 320;

constexpr int OFF_SC = NSTAGE * STAGE_BYTES;
constexpr int OFF_RED = OFF_SC + 9216;
constexpr int OFF_PF = OFF_RED;
constexpr int OFF_Q = OFF_RED + 8192;
constexpr int OFF_MISC = OFF_Q + 1024;
constexpr int OFF_BAR = OFF_MISC + 256;
constexpr int SMEM_USED = OFF_BAR + 256;
constexpr int SMEM_BYTES = SMEM_USED + 1024;

constexpr unsigned SPIN_LIMIT = 1u << 22;

struct Scratch {
    uint4 o[16 * 16 * 32];
    uint4 h[NPROJ * 32];
    uint2 q[NB * 2048];
    uint2 box[8 * NB * DM];
    unsigned long long acc[NB * DM];
    unsigned epoch[NCTA];
    unsigned late[2][32];
};
__device__ Scratch g_scratch;

struct Params {
    Scratch* sc;
    const __nv_bfloat16 *wq, *x, *gate_w, *b1, *b2;
    __nv_bfloat16* out;
    int tau, lead, gate, a16, target;
};

#define TLW(i, w)
#define TLMAX(i)

__device__ __forceinline__ uint32_t smem_u32(const void* p) { return (uint32_t)__cvta_generic_to_shared(p); }
__device__ __forceinline__ void mbar_init(uint32_t bar, int cnt) {
    asm volatile("mbarrier.init.shared::cta.b64 [%0], %1;" ::"r"(bar), "r"(cnt) : "memory");
}
__device__ __forceinline__ void mbar_expect_tx(uint32_t bar, uint32_t bytes) {
    asm volatile("mbarrier.arrive.expect_tx.shared::cta.b64 _, [%0], %1;" ::"r"(bar), "r"(bytes) : "memory");
}
__device__ __forceinline__ void mbar_arrive(uint32_t bar) {
    asm volatile("mbarrier.arrive.shared::cta.b64 _, [%0];" ::"r"(bar) : "memory");
}
__device__ __forceinline__ void mbar_arrive_n(uint32_t bar, uint32_t n) {
    asm volatile("mbarrier.arrive.shared::cta.b64 _, [%0], %1;" ::"r"(bar), "r"(n) : "memory");
}
__device__ __forceinline__ void st_async2(uint32_t addr, float a, float b, uint32_t bar) {
    asm volatile("st.async.weak.shared::cluster.mbarrier::complete_tx::bytes.v2.f32 [%0], {%1, %2}, [%3];"
                 ::"r"(addr), "f"(a), "f"(b), "r"(bar) : "memory");
}
__device__ __forceinline__ void mbar_wait(uint32_t bar, uint32_t parity) {
    uint32_t done;
    unsigned n = 0;
    do {
        asm volatile("{\n.reg .pred p;\nmbarrier.try_wait.parity.shared::cta.b64 p, [%1], %2;\nselp.u32 %0, 1, 0, p;\n}"
                     : "=r"(done) : "r"(bar), "r"(parity) : "memory");
        if (++n > SPIN_LIMIT) __trap();
    } while (!done);
}
__device__ __forceinline__ void tma2d(uint32_t dst, const CUtensorMap* tm, int c0, int c1, uint32_t bar, uint64_t pol) {
    asm volatile("cp.async.bulk.tensor.2d.shared::cluster.global.mbarrier::complete_tx::bytes.L2::cache_hint [%0], [%1, {%3, %4}], [%2], %5;"
                 ::"r"(dst), "l"(tm), "r"(bar), "r"(c0), "r"(c1), "l"(pol) : "memory");
}
__device__ __forceinline__ void tma3d(uint32_t dst, const CUtensorMap* tm, int c0, int c1, int c2, uint32_t bar, uint64_t pol) {
    asm volatile("cp.async.bulk.tensor.3d.shared::cluster.global.mbarrier::complete_tx::bytes.L2::cache_hint [%0], [%1, {%3, %4, %5}], [%2], %6;"
                 ::"r"(dst), "l"(tm), "r"(bar), "r"(c0), "r"(c1), "r"(c2), "l"(pol) : "memory");
}
__device__ __forceinline__ void ldsm4(uint32_t (&r)[4], uint32_t addr) {
    asm volatile("ldmatrix.sync.aligned.m8n8.x4.shared.b16 {%0,%1,%2,%3}, [%4];"
                 : "=r"(r[0]), "=r"(r[1]), "=r"(r[2]), "=r"(r[3]) : "r"(addr) : "memory");
}
__device__ __forceinline__ void ldsm4t(uint32_t (&r)[4], uint32_t addr) {
    asm volatile("ldmatrix.sync.aligned.m8n8.x4.trans.shared.b16 {%0,%1,%2,%3}, [%4];"
                 : "=r"(r[0]), "=r"(r[1]), "=r"(r[2]), "=r"(r[3]) : "r"(addr) : "memory");
}
__device__ __forceinline__ void mma16816(float (&c)[4], uint32_t a0, uint32_t a1, uint32_t a2, uint32_t a3, uint32_t b0, uint32_t b1) {
    asm volatile("mma.sync.aligned.m16n8k16.row.col.f32.bf16.bf16.f32 {%0,%1,%2,%3}, {%4,%5,%6,%7}, {%8,%9}, {%0,%1,%2,%3};"
                 : "+f"(c[0]), "+f"(c[1]), "+f"(c[2]), "+f"(c[3])
                 : "r"(a0), "r"(a1), "r"(a2), "r"(a3), "r"(b0), "r"(b1));
}
__device__ __forceinline__ void cons_sync() { asm volatile("bar.sync 1, 256;" ::: "memory"); }

__device__ __forceinline__ float bf16r(float v) { return __bfloat162float(__float2bfloat16_rn(v)); }
__device__ __forceinline__ uint32_t pack_bf16(float lo, float hi) {
    uint32_t r;
    asm("cvt.rn.bf16x2.f32 %0, %1, %2;" : "=r"(r) : "f"(hi), "f"(lo));
    return r;
}
__device__ __forceinline__ float bf_lo(uint32_t w) { return __uint_as_float(w << 16); }
__device__ __forceinline__ float bf_hi(uint32_t w) { return __uint_as_float(w & 0xffff0000u); }

__device__ __forceinline__ void st_pkt8(uint2* p, uint32_t d, uint32_t tag) {
    unsigned long long v = ((unsigned long long)tag << 32) | d;
    asm volatile("st.relaxed.gpu.global.b64 [%0], %1;" ::"l"(p), "l"(v) : "memory");
}
__device__ __forceinline__ uint32_t poll_pkt8(const uint2* p, uint32_t tag) {
    unsigned long long v;
    for (unsigned n = 0;; n++) {
        asm volatile("ld.relaxed.gpu.global.b64 %0, [%1];" : "=l"(v) : "l"(p) : "memory");
        if ((uint32_t)(v >> 32) == tag) break;
        if (n > SPIN_LIMIT) __trap();
    }
    return (uint32_t)v;
}
__device__ __forceinline__ void st_pkt16(uint4* p, uint32_t d0, uint32_t d1, uint32_t tag) {
    unsigned long long lo = ((unsigned long long)d1 << 32) | d0, hi = tag;
    asm volatile("{\n.reg .b128 t;\nmov.b128 t, {%1, %2};\nst.relaxed.gpu.global.b128 [%0], t;\n}" ::"l"(p), "l"(lo), "l"(hi) : "memory");
}
__device__ __forceinline__ void ld_pkt16(const uint4* p, unsigned long long& lo, unsigned long long& hi) {
    asm volatile("{\n.reg .b128 t;\nld.relaxed.gpu.global.b128 t, [%2];\nmov.b128 {%0, %1}, t;\n}" : "=l"(lo), "=l"(hi) : "l"(p) : "memory");
}
__device__ __forceinline__ void reld_pkt16(const uint4* p, unsigned long long& lo, unsigned long long& hi, bool need) {
    asm volatile("{\n.reg .b128 t;\n.reg .pred p;\nsetp.ne.u32 p, %3, 0;\nmov.b128 t, {%0, %1};\n@p ld.relaxed.gpu.global.b128 t, [%2];\nmov.b128 {%0, %1}, t;\n}"
                 : "+l"(lo), "+l"(hi) : "l"(p), "r"((uint32_t)need) : "memory");
}
__device__ __forceinline__ bool mbar_test(uint32_t bar, uint32_t parity) {
    uint32_t done;
    asm volatile("{\n.reg .pred p;\nmbarrier.test_wait.parity.shared::cta.b64 p, [%1], %2;\nselp.u32 %0, 1, 0, p;\n}"
                 : "=r"(done) : "r"(bar), "r"(parity) : "memory");
    return done;
}
__device__ __forceinline__ uint32_t pin(uint32_t v) { return __shfl_sync(~0u, v, threadIdx.x & 31); }
template <class T>
__device__ __forceinline__ T* pin(T* p) {
    return reinterpret_cast<T*>(__shfl_sync(~0u, reinterpret_cast<unsigned long long>(p), threadIdx.x & 31));
}
template <int N, int S>
__device__ __forceinline__ void gather_pkts(const uint4* p, uint32_t tag, unsigned long long (&lo)[N]) {
    unsigned long long hi[N];
#pragma unroll
    for (int i = 0; i < N; i++) ld_pkt16(p + 32 * (i & 1) + S * (i >> 1), lo[i], hi[i]);
    for (unsigned n = 0;; n++) {
        bool need[N], any = false;
#pragma unroll
        for (int i = 0; i < N; i++) { need[i] = (uint32_t)hi[i] != tag; any |= need[i]; }
        if (!__any_sync(~0u, any)) break;
#pragma unroll
        for (int i = 0; i < N; i++) reld_pkt16(p + 32 * (i & 1) + S * (i >> 1), lo[i], hi[i], need[i]);
        if (n > SPIN_LIMIT) __trap();
    }
}
__device__ __forceinline__ unsigned long long acc_encode(float v, int flags) {
    const float th = __fadd_rn(v, 12288.f);
    const float tl = __fadd_rn(__fsub_rn(v, __fsub_rn(th, 12288.f)), 0.0029296875f);
    const int hi = __float_as_int(th) - 0x46400000, lo = __float_as_int(tl) - 0x3b400000;
    return (unsigned long long)((long long)lo * 65536 + flags) + ((unsigned long long)(uint32_t)(hi << 6) << 32);
}
__device__ __forceinline__ float acc_decode(unsigned long long tot) {
    return fmaf((float)(int)(tot >> 32), 0x1p-16f, (float)((uint32_t)tot >> 16) * 0x1p-32f);
}

__global__ void __cluster_dims__(2, 1, 1) __launch_bounds__(NTHREADS, 1)
fused_kernel(const __grid_constant__ Params P, const __grid_constant__ CUtensorMap tmWq,
             const __grid_constant__ CUtensorMap tmK, const __grid_constant__ CUtensorMap tmV,
             const __grid_constant__ CUtensorMap tmW1, const __grid_constant__ CUtensorMap tmW2,
             const __grid_constant__ CUtensorMap tmWo) {
    extern __shared__ unsigned char smem_raw[];
    const uint32_t raw = smem_u32(smem_raw);
    const uint32_t sb = (raw + 1023u) & ~1023u;
    unsigned char* sp = smem_raw + (sb - raw);

    const int tid = threadIdx.x, warp = tid >> 5, lane = tid & 31;
    const int g = lane >> 2, t = lane & 3;
    const int j = blockIdx.x;
    const int hkv = j >> 4, bb = (j >> 1) & 7, s = j & 1;
    const bool proj = j < NPROJ;
    const int pk = j / 14, pc = j - pk * 14;

    const uint32_t bar_full = sb + OFF_BAR, bar_empty = bar_full + 8 * NSTAGE, bar_sc = bar_empty + 8 * NSTAGE;

    if (warp == 9) {
        const uint32_t ep = *reinterpret_cast<volatile unsigned*>(&P.sc->epoch[j]);
        if (lane == 0) asm volatile("st.shared.v2.u32 [%0], {%1, 0};" ::"r"(sb + OFF_MISC + 232), "r"(ep) : "memory");
        asm volatile("barrier.cluster.arrive.relaxed.aligned;" ::: "memory");
        asm volatile("barrier.cluster.wait.acquire.aligned;" ::: "memory");
        if (lane == 0) {
            unsigned* slot = &P.sc->late[ep & 1][0];
            if (j == 0) P.sc->late[(ep ^ 1) & 1][0] = 0;
            mbar_wait(bar_full + 8 * (MTILE % NSTAGE), ((MTILE / NSTAGE) & 1) ^ 1);
            mbar_wait(bar_full + 8 * (MTILE % NSTAGE), (MTILE / NSTAGE) & 1);
            uint32_t now, t0, v;
            asm volatile("mov.u32 %0, %%globaltimer_lo;" : "=r"(now));
            asm volatile("ld.volatile.shared.u32 %0, [%1];" : "=r"(t0) : "r"(sb + OFF_MISC + 244) : "memory");
            const int lat = min(max((int)(now - t0) - (MTILE * P.tau - P.lead), 0), 6000);
            asm volatile("red.relaxed.gpu.global.add.u32 [%0], %1;" ::"l"(slot), "r"((1u << 20) + lat) : "memory");
            do { __nanosleep(100); asm volatile("mov.u32 %0, %%globaltimer_lo;" : "=r"(now)); } while ((int)(now - t0) < RTILE * P.tau - P.lead);
            asm volatile("ld.relaxed.gpu.global.u32 %0, [%1];" : "=r"(v) : "l"(slot) : "memory");
            const int mean = ((int)(v & 0xfffffu) + (NCTA - (int)(v >> 20)) * (RTILE - MTILE) * P.tau) / NCTA;
            const int shift = min(max(((mean - P.target) * P.a16) >> 4, -P.tau), 3 * P.tau);
            asm volatile("st.volatile.shared.u32 [%0], %1;" ::"r"(sb + OFF_MISC + 236), "r"(shift) : "memory");
        }
        return;
    }
    if (warp == 8) {
        TLW(20, 8);
        int tau = P.tau, lead = P.lead;
        uint64_t pol;
        asm volatile("createpolicy.fractional.L2::evict_first.b64 %0, 1.0;" : "=l"(pol));
        const int row0 = (bb * 8 + hkv) * SK + (SK - WIN);
        if (lane == 0) {
#pragma unroll
            for (int i = 0; i < NEARLY; i++) mbar_init(bar_full + 8 * i, 1);
            asm volatile("fence.proxy.async.shared::cta;" ::: "memory");
            TLW(21, 8);
            mbar_expect_tx(bar_full, STAGE_BYTES);
            tma2d(sb, &tmWq, 32 * j, 0, bar_full, pol);
            TLW(22, 8);
            mbar_expect_tx(bar_full + 8, STAGE_BYTES);
            tma2d(sb + STAGE_BYTES, &tmWq, 32 * j, 256, bar_full + 8, pol);
#pragma unroll
            for (int i = 2; i < NEARLY; i++) {
                mbar_expect_tx(bar_full + 8 * i, STAGE_BYTES);
                tma3d(sb + i * STAGE_BYTES, &tmK, 0, row0 + s * 512 + (i - 2) * 32, 0, bar_full + 8 * i, pol);
            }
            TLW(23, 8);
            asm volatile("prefetch.tensormap [%0];" ::"l"(&tmK) : "memory");
            asm volatile("prefetch.tensormap [%0];" ::"l"(&tmV) : "memory");
            asm volatile("prefetch.tensormap [%0];" ::"l"(&tmW1) : "memory");
            asm volatile("prefetch.tensormap [%0];" ::"l"(&tmW2) : "memory");
            asm volatile("prefetch.tensormap [%0];" ::"l"(&tmWo) : "memory");
#pragma unroll
            for (int i = NEARLY; i < NSTAGE; i++) mbar_init(bar_full + 8 * i, 1);
#pragma unroll
            for (int i = 0; i < NSTAGE; i++) mbar_init(bar_empty + 8 * i, 8);
            mbar_init(bar_sc, 1);
            asm volatile("fence.mbarrier_init.release.cluster;" ::: "memory");
            asm volatile("fence.proxy.async.shared::cta;" ::: "memory");
        }
        __syncwarp();
        asm volatile("barrier.cluster.arrive.relaxed.aligned;" ::: "memory");
        if (lane == 0) {
            uint32_t t0;
            asm volatile("mov.u32 %0, %%globaltimer_lo;" : "=r"(t0));
            asm volatile("st.shared.u32 [%0], %1;" ::"r"(sb + OFF_MISC + 244), "r"(t0) : "memory");
            mbar_expect_tx(bar_sc, 8192);
            const int ntiles = proj ? 38 : 35;
            int st = NEARLY, par = 1, wst = 0, wpar = 0, arrived = 0;
            for (int i = NEARLY; i < ntiles; i++) {
                while (arrived <= i - WINDOW) {
                    mbar_wait(bar_full + 8 * wst, wpar);
                    if (++wst == NSTAGE) { wst = 0; wpar ^= 1; }
                    arrived++;
                }
                if (i >= NSTAGE) mbar_wait(bar_empty + 8 * st, par);
                {
                    const int due = i * tau - lead;
                    uint32_t now;
                    int shift = 0;
                    do {
                        if (i > RTILE) asm volatile("ld.volatile.shared.u32 %0, [%1];" : "=r"(shift) : "r"(sb + OFF_MISC + 236) : "memory");
                        asm volatile("mov.u32 %0, %%globaltimer_lo;" : "=r"(now));
                    } while ((int)(now - t0) < due + shift);
                }
                const uint32_t dst = sb + st * STAGE_BYTES, bar = bar_full + 8 * st;
                if (i == 18) {
                    if (proj) {
                        mbar_expect_tx(bar, STAGE_BYTES);
                        tma2d(dst, &tmW1, 16 * j, 0, bar, pol);
                        tma2d(dst + 8192, &tmW1, 16 * j, 256, bar, pol);
                    } else {
                        mbar_arrive(bar);
                    }
                } else {
                    mbar_expect_tx(bar, i == 35 ? 224 * 64 : STAGE_BYTES);
                    if (i < 35) {
                        const bool isk = i < 18;
                        tma3d(dst, isk ? &tmK : &tmV, 0, isk ? row0 + s * 512 + (i - 2) * 32 : row0 + (i - 19) * 64, isk ? 0 : 2 * s, bar, pol);
                    } else {
                        tma2d(dst, i == 35 ? &tmW2 : &tmWo, pc * 32, i == 35 ? pk * 224 : pk * 512 + (i - 36) * 256, bar, pol);
                    }
                }
                if (i == 34) TLW(25, 8);
                if (i == 37) TLW(26, 8);
                if (++st == NSTAGE) { st = 0; par ^= 1; }
            }
        }
        __syncwarp();
        asm volatile("barrier.cluster.wait.acquire.aligned;" ::: "memory");
        return;
    }

    TLW(0, 0);
    Scratch* sc = P.sc;
    const __nv_bfloat16 *x = P.x, *gate_w = P.gate_w, *b1 = P.b1, *b2 = P.b2;
    __nv_bfloat16* out = P.out;
    if (tid == 224) asm volatile("st.shared.u32 [%0], %1;" ::"r"(sb + OFF_MISC + 252), "r"(P.tau) : "memory");
    if (lane == 0 && warp < 2)
        asm volatile("cp.async.bulk.prefetch.L2.global [%0], %1;"
                     ::"l"(reinterpret_cast<const char*>(P.wq) + (size_t)j * 28672 + warp * 14336), "r"(14336) : "memory");
    uint2* q_slot = &sc->q[(tid >> 4) * 2048 + 16 * j + (tid & 15)];
    if (tid < 128) st_pkt8(q_slot, 0u, 0u);
    uint32_t tag = *reinterpret_cast<volatile unsigned*>(&sc->epoch[j]);
    uint32_t xb[8];
    {
        const uint32_t* xp = reinterpret_cast<const uint32_t*>(x + g * DM) + (warp < 7 ? warp : 0) * 32 + t;
#pragma unroll
        for (int i = 0; i < 8; i++) xb[i] = __ldg(xp + 4 * i);
    }
    uint32_t xw[7], gw[7];
#pragma unroll
    for (int i = 0; i < 7; i++) {
        xw[i] = __ldg(reinterpret_cast<const uint32_t*>(x + warp * DM) + lane + 32 * i);
        gw[i] = __ldg(reinterpret_cast<const uint32_t*>(gate_w) + lane + 32 * i);
    }
    uint32_t b1w = 0;
    float b2v = 0.f;
    if (proj) {
        b1w = __ldg(reinterpret_cast<const uint32_t*>(b1 + 16 * j) + (tid & 7));
        b2v = __bfloat162float(b2[pc * 32 + lane]);
    }
    asm volatile("barrier.cluster.arrive.relaxed.aligned;" ::: "memory");
    asm volatile("barrier.cluster.wait.acquire.aligned;" ::: "memory");
    TLW(48, 0);
    float* misc = reinterpret_cast<float*>(sp + OFF_MISC);
    float* red = reinterpret_cast<float*>(sp + OFF_RED);
    const int r = lane & 7, mi = lane >> 3;
    if (warp < 7) {
        float c[2][4] = {};
        const int row = warp * 64 + r + 8 * (mi >> 1);
        const uint32_t qa0 = sb + row * 64 + (((mi & 1) ^ ((r >> 1) & 3)) << 4);
        const uint32_t qa1 = sb + row * 64 + (((2 + (mi & 1)) ^ ((r >> 1) & 3)) << 4);
        mbar_wait(bar_full + 8 * (warp >> 2), 0);
        TLW(61, 0);
#pragma unroll
        for (int ks = 0; ks < 4; ks++) {
            uint32_t a0[4], a1[4];
            ldsm4t(a0, qa0 + ks * 1024);
            ldsm4t(a1, qa1 + ks * 1024);
            mma16816(c[0], a0[0], a0[1], a0[2], a0[3], xb[2 * ks], xb[2 * ks + 1]);
            mma16816(c[1], a1[0], a1[1], a1[2], a1[3], xb[2 * ks], xb[2 * ks + 1]);
        }
        float* r0 = red + (warp * 8 + 2 * t) * 36 + g;
#pragma unroll
        for (int mt = 0; mt < 2; mt++) {
            r0[16 * mt] = c[mt][0];
            r0[36 + 16 * mt] = c[mt][1];
            r0[16 * mt + 8] = c[mt][2];
            r0[36 + 16 * mt + 8] = c[mt][3];
        }
    }
    TLMAX(53);
    cons_sync();
    tag = tag + 1u == 0u ? 2u : tag + 1u;
    if (tid < 128) {
        float v0 = 0.f, v1 = 0.f;
#pragma unroll
        for (int w = 0; w < 7; w++) {
            const float2 v = *reinterpret_cast<const float2*>(red + (w * 8 + (tid >> 4)) * 36 + 2 * (tid & 15));
            v0 += v.x; v1 += v.y;
        }
        st_pkt8(q_slot, pack_bf16(v0, v1), tag);
    } else if (tid >= 224 && tid < 226) {
        mbar_arrive_n(bar_empty + 8 * (tid - 224), 8);
    }
    TLW(1, 0);
    {
        float sum = 0.f, gs = 0.f;
#pragma unroll
        for (int i = 0; i < 7; i++) {
            sum += bf_lo(xw[i]) + bf_hi(xw[i]);
            gs += bf16r(bf_lo(xw[i]) * bf_lo(gw[i])) + bf16r(bf_hi(xw[i]) * bf_hi(gw[i]));
        }
#pragma unroll
        for (int o = 16; o; o >>= 1) { sum += __shfl_xor_sync(~0u, sum, o); gs += __shfl_xor_sync(~0u, gs, o); }
        const float mean = sum * (1.f / DM);
        float vs = 0.f;
#pragma unroll
        for (int i = 0; i < 7; i++) {
            const float d0 = bf_lo(xw[i]) - mean, d1 = bf_hi(xw[i]) - mean;
            vs += d0 * d0 + d1 * d1;
        }
#pragma unroll
        for (int o = 16; o; o >>= 1) vs += __shfl_xor_sync(~0u, vs, o);
        if (lane == 0) {
            const float gt = bf16r(__fdividef(1.f, 1.f + __expf(-bf16r(gs))));
            misc[warp] = gt;
            misc[8 + warp] = bf16r(1.f - gt);
            misc[32 + warp] = bf16r(mean);
            misc[40 + warp] = bf16r(__fsqrt_rn(bf16r(bf16r(vs * (1.f / DM)) + 1e-5f)));
        }
    }
    reinterpret_cast<uint32_t*>(sp + OFF_Q)[tid] = poll_pkt8(&sc->q[bb * 2048 + hkv * 256 + tid], tag);
    TLW(55, 0); TLMAX(56);
    cons_sync();
    if (tid == 0) sc->epoch[j] = tag;

    {
        uint32_t qa[16][2];
        const uint32_t* qs = reinterpret_cast<const uint32_t*>(sp + OFF_Q) + (g & 1) * 128 + t;
#pragma unroll
        for (int ks = 0; ks < 16; ks++) { qa[ks][0] = qs[ks * 8]; qa[ks][1] = qs[ks * 8 + 4]; }
        const uint32_t a_even = ((warp & 3) * 8 + r) * 128 + ((mi ^ r) << 4);
        const uint32_t a_odd = ((warp & 3) * 8 + r) * 128 + (((mi + 4) ^ r) << 4);
        const uint32_t sc_local = sb + OFF_SC + (g & 1) * 4096 + ((s * 16 + (warp >> 2)) * 4 + t) * 32 + (warp & 3) * 8;
        uint32_t sc_dst, bar_dst;
        asm("mapa.shared::cluster.u32 %0, %1, %2;" : "=r"(sc_dst) : "r"(sc_local), "r"((g >> 1) & 1));
        asm("mapa.shared::cluster.u32 %0, %1, %2;" : "=r"(bar_dst) : "r"(bar_sc), "r"((g >> 1) & 1));
        int st = 2 + (warp >> 2), par = 0;
        for (int i = 0; i < 8; i++) {
            mbar_wait(bar_full + 8 * st, par);
            TLW(8 + i, 0);
            const uint32_t base = sb + st * STAGE_BYTES;
            float ca[4] = {}, cb[4] = {}, cc[4] = {}, cd[4] = {};
#pragma unroll
            for (int c = 0; c < 4; c++) {
                uint32_t k0[4], k1[4];
                ldsm4(k0, base + c * 4096 + a_even);
                ldsm4(k1, base + c * 4096 + a_odd);
                mma16816(ca, qa[4 * c][0], qa[4 * c][0], qa[4 * c][1], qa[4 * c][1], k0[0], k0[1]);
                mma16816(cb, qa[4 * c + 1][0], qa[4 * c + 1][0], qa[4 * c + 1][1], qa[4 * c + 1][1], k0[2], k0[3]);
                mma16816(cc, qa[4 * c + 2][0], qa[4 * c + 2][0], qa[4 * c + 2][1], qa[4 * c + 2][1], k1[0], k1[1]);
                mma16816(cd, qa[4 * c + 3][0], qa[4 * c + 3][0], qa[4 * c + 3][1], qa[4 * c + 3][1], k1[2], k1[3]);
            }
            __syncwarp();
            if (lane == 0) mbar_arrive_n(bar_empty + 8 * st, 2);
            if (g < 4) {
                const float s0 = bf16r((ca[0] + cb[0]) + (cc[0] + cd[0])) * 0.0625f;
                const float s1 = bf16r((ca[1] + cb[1]) + (cc[1] + cd[1])) * 0.0625f;
                st_async2(sc_dst + i * 256, s0, s1, bar_dst);
            }
            st += 2;
            if (st >= NSTAGE) { st -= NSTAGE; par ^= 1; }
        }
    }
    TLW(58, 0);
    uint4* o_slot = &sc->o[(((2 * hkv + (g & 1)) * 16 + s * 8 + warp) * 8 + bb) * 4 + (g >> 1)];
    if (t == 0) st_pkt16(o_slot, 0u, 0u, 0u);
    if (proj && warp == 4) {
        const float bv = misc[8 + pk] * b2v;
        const bool fits = fabsf(bv) < 2048.f;
        asm volatile("red.relaxed.gpu.global.add.u64 [%0], %1;"
                     ::"l"(&sc->acc[pk * DM + pc * 32 + lane]), "l"(acc_encode(fits ? bv : 0.f, fits ? 1 : 257)) : "memory");
    }
    int st = 18 % NSTAGE, par = (18 / NSTAGE) & 1;
    {
        if (proj || tid == 224) mbar_wait(bar_full + 8 * st, par);
        if (proj) {
            if (warp < 7) {
                const float mb = misc[32 + g], sd = misc[40 + g];
                const uint32_t ha = sb + st * STAGE_BYTES + (warp * 64 + r + 8 * (mi >> 1)) * 32 + (((mi & 1) ^ (r >> 2)) << 4);
                float c[4] = {};
#pragma unroll
                for (int ks = 0; ks < 4; ks++) {
                    uint32_t a2[4], y[2];
                    ldsm4t(a2, ha + ks * 512);
#pragma unroll
                    for (int i = 0; i < 2; i++)
                        y[i] = pack_bf16(__fdividef(bf16r(bf_lo(xb[2 * ks + i]) - mb), sd), __fdividef(bf16r(bf_hi(xb[2 * ks + i]) - mb), sd));
                    mma16816(c, a2[0], a2[1], a2[2], a2[3], y[0], y[1]);
                }
                float* r0 = red + (warp * 8 + 2 * t) * 36 + g;
                r0[0] = c[0]; r0[36] = c[1]; r0[8] = c[2]; r0[44] = c[3];
            }
            cons_sync();
            if (tid < 64) {
                const int b = tid >> 3, cp = tid & 7;
                float v[2] = {0.f, 0.f};
#pragma unroll
                for (int w = 0; w < 7; w++) {
                    const float2 u = *reinterpret_cast<const float2*>(red + (w * 8 + b) * 36 + 2 * cp);
                    v[0] += u.x; v[1] += u.y;
                }
                v[0] = bf16r(bf16r(v[0]) + bf_lo(b1w));
                v[1] = bf16r(bf16r(v[1]) + bf_hi(b1w));
#pragma unroll
                for (int i = 0; i < 2; i++) {
                    const float u = v[i];
                    v[i] = __fdividef(u, 1.f + __expf(-1.5957691216057308f * (u + 0.044715f * u * u * u)));
                }
                const uint32_t w0 = pack_bf16(v[0], v[1]);
                const uint32_t w1w = __shfl_down_sync(~0u, w0, 4);
                if (cp < 4) st_pkt16(&sc->h[j * 32 + b * 4 + cp], w0, w1w, tag);
            }
        }
        if (tid == 224) mbar_arrive_n(bar_empty + 8 * st, 8);
        if (++st == NSTAGE) { st = 0; par ^= 1; }
    }
    TLW(60, 0);
    mbar_wait(bar_sc, 0);
    TLW(3, 0);
    {
        const float4* scp = reinterpret_cast<const float4*>(sp + OFF_SC) + tid * 2;
        const float4 u0 = scp[0], u1 = scp[1];
        float e[8] = {u0.x, u0.y, u0.z, u0.w, u1.x, u1.y, u1.z, u1.w};
        float m = e[0];
#pragma unroll
        for (int i = 1; i < 8; i++) m = fmaxf(m, e[i]);
#pragma unroll
        for (int o = 16; o; o >>= 1) m = fmaxf(m, __shfl_xor_sync(~0u, m, o));
        if (lane == 0) misc[16 + warp] = m;
        cons_sync();
        const float4 mm = *reinterpret_cast<const float4*>(misc + 16 + (warp & 4));
        m = fmaxf(fmaxf(mm.x, mm.y), fmaxf(mm.z, mm.w));
        float l = 0.f;
#pragma unroll
        for (int i = 0; i < 8; i++) { e[i] = __expf(e[i] - m); l += e[i]; }
#pragma unroll
        for (int o = 16; o; o >>= 1) l += __shfl_xor_sync(~0u, l, o);
        if (lane == 0) misc[24 + warp] = l;
        cons_sync();
        const float4 ll = *reinterpret_cast<const float4*>(misc + 24 + (warp & 4));
        const float inv = __fdividef(1.f, (ll.x + ll.y) + (ll.z + ll.w));
        reinterpret_cast<uint4*>(sp + OFF_PF)[tid] =
            make_uint4(pack_bf16(e[0] * inv, e[1] * inv), pack_bf16(e[2] * inv, e[3] * inv),
                       pack_bf16(e[4] * inv, e[5] * inv), pack_bf16(e[6] * inv, e[7] * inv));
        cons_sync();
    }
    unsigned long long hv[2] = {0ull, 0ull};
    const uint32_t trow = (r + 8 * (mi >> 1)) * 128;
    {
        float ca[4] = {}, cb[4] = {};
        const uint32_t va = (warp >> 2) * 8192 + trow + (((2 * (warp & 3) + (mi & 1)) ^ r) << 4);
        const uint4* pf = reinterpret_cast<const uint4*>(sp + OFF_PF) + (g & 1) * 128 + t;
        for (int i = 0; i < 16; i++) {
            const uint4 pw0 = pf[i * 8], pw1 = pf[i * 8 + 4];
            mbar_wait(bar_full + 8 * st, par);
            TLW(32 + i, 0);
            const uint32_t base = sb + st * STAGE_BYTES + va;
            uint32_t v0[4], v1[4], v2[4], v3[4];
            ldsm4t(v0, base);
            ldsm4t(v1, base + 2048);
            ldsm4t(v2, base + 4096);
            ldsm4t(v3, base + 6144);
            mma16816(ca, v0[0], v0[1], v0[2], v0[3], pw0.x, pw0.y);
            mma16816(cb, v1[0], v1[1], v1[2], v1[3], pw0.z, pw0.w);
            mma16816(ca, v2[0], v2[1], v2[2], v2[3], pw1.x, pw1.y);
            mma16816(cb, v3[0], v3[1], v3[2], v3[3], pw1.z, pw1.w);
            __syncwarp();
            if (lane == 0) mbar_arrive(bar_empty + 8 * st);
            if (++st == NSTAGE) { st = 0; par ^= 1; }
            if (i == HPOS && proj && warp < 7) gather_pkts<2, 0>(&sc->h[(pk * 14 + 2 * warp) * 32 + lane], tag, hv);
        }
#pragma unroll
        for (int i = 0; i < 4; i++) ca[i] += cb[i];
        const bool odd = g & 1;
        const float n0 = __shfl_xor_sync(~0u, odd ? ca[0] : ca[1], 4);
        const float n1 = __shfl_xor_sync(~0u, odd ? ca[2] : ca[3], 4);
        const uint32_t w0 = odd ? pack_bf16(n0, ca[1]) : pack_bf16(ca[0], n0);
        const uint32_t w1w = odd ? pack_bf16(n1, ca[3]) : pack_bf16(ca[2], n1);
        if (t == 0) st_pkt16(o_slot, w0, w1w, tag);
    }
    TLMAX(18);
    if (proj) {
        constexpr int S35 = 35 % NSTAGE, P35 = (35 / NSTAGE) & 1, S36 = 36 % NSTAGE, P36 = (36 / NSTAGE) & 1,
                      S37 = 37 % NSTAGE, P37 = (37 / NSTAGE) & 1;
        const uint32_t wa0 = pin(sb + (warp * 32 + r + 8 * (mi >> 1)) * 64 + (((mi & 1) ^ ((r >> 1) & 3)) << 4));
        const uint32_t wa1 = wa0 ^ 32u;
        const int e = warp * DM + pc * 32 + lane;
        unsigned long long* accp = pin(&sc->acc[e]);
        __nv_bfloat16* outp = pin(out + e);
        const uint32_t rw = pin(sb + OFF_SC + ((warp * 8 + 2 * t) * 36 + g) * 4), rr = pin(sb + OFF_SC + (warp * 36 + lane) * 4);
        const uint4* op = pin(&sc->o[(pk * 32 + 2 * warp) * 32 + lane]);
        float acm[2][4] = {}, acc[2][2][4] = {};
        const float g0 = misc[2 * t], g1 = misc[2 * t + 1], m0 = misc[8 + 2 * t], m1 = misc[8 + 2 * t + 1];
        uint32_t aa[8][4];
        mbar_wait(bar_full + 8 * S35, P35);
        if (warp < 7) {
#pragma unroll
            for (int ks = 0; ks < 2; ks++) {
                ldsm4t(aa[0], wa0 + S35 * STAGE_BYTES + ks * 1024);
                ldsm4t(aa[1], wa1 + S35 * STAGE_BYTES + ks * 1024);
                mma16816(acm[0], aa[0][0], aa[0][1], aa[0][2], aa[0][3], (uint32_t)hv[ks], (uint32_t)(hv[ks] >> 32));
                mma16816(acm[1], aa[1][0], aa[1][1], aa[1][2], aa[1][3], (uint32_t)hv[ks], (uint32_t)(hv[ks] >> 32));
            }
        }
        unsigned long long ov[4], oh[4];
        {
            const uint32_t tg = *reinterpret_cast<volatile uint32_t*>(misc + 61) + *reinterpret_cast<volatile uint32_t*>(misc + 59) + P.gate;
            uint32_t now;
            do { asm volatile("mov.u32 %0, %%globaltimer_lo;" : "=r"(now)); } while ((int)(now - tg) < 0);
        }
#pragma unroll
        for (int i = 0; i < 4; i++) ld_pkt16(op + 32 * (i & 1) + 512 * (i >> 1), ov[i], oh[i]);
        int have = 0;
        TLW(110, 0);
        for (unsigned n = 0;; n++) {
            if (have == 0 && __all_sync(~0u, mbar_test(bar_full + 8 * S36, P36))) {
                have = 1;
#pragma unroll
                for (int i = 0; i < 4; i++) ldsm4t(aa[i], ((i & 1) ? wa1 : wa0) + S36 * STAGE_BYTES + (i >> 1) * 1024);
            }
            if (have == 1 && __all_sync(~0u, mbar_test(bar_full + 8 * S37, P37))) {
                have = 2;
#pragma unroll
                for (int i = 0; i < 4; i++) ldsm4t(aa[4 + i], ((i & 1) ? wa1 : wa0) + S37 * STAGE_BYTES + (i >> 1) * 1024);
            }
            bool need[4], any = false;
#pragma unroll
            for (int i = 0; i < 4; i++) { need[i] = (uint32_t)oh[i] != tag; any |= need[i]; }
            if (!__any_sync(~0u, any)) break;
#pragma unroll
            for (int i = 0; i < 4; i++) reld_pkt16(op + 32 * (i & 1) + 512 * (i >> 1), ov[i], oh[i], need[i]);
            if (n > SPIN_LIMIT) __trap();
        }
        TLMAX(16);
        if (have == 0) {
            mbar_wait(bar_full + 8 * S36, P36);
#pragma unroll
            for (int i = 0; i < 4; i++) ldsm4t(aa[i], ((i & 1) ? wa1 : wa0) + S36 * STAGE_BYTES + (i >> 1) * 1024);
        }
#pragma unroll
        for (int i = 0; i < 4; i++)
            mma16816(acc[i & 1][(i >> 1) & 1], aa[i][0], aa[i][1], aa[i][2], aa[i][3], (uint32_t)ov[i >> 1], (uint32_t)(ov[i >> 1] >> 32));
        if (have < 2) {
            mbar_wait(bar_full + 8 * S37, P37);
#pragma unroll
            for (int i = 0; i < 4; i++) ldsm4t(aa[4 + i], ((i & 1) ? wa1 : wa0) + S37 * STAGE_BYTES + (i >> 1) * 1024);
        }
        TLMAX(17);
#pragma unroll
        for (int i = 4; i < 8; i++)
            mma16816(acc[i & 1][(i >> 1) & 1], aa[i][0], aa[i][1], aa[i][2], aa[i][3], (uint32_t)ov[i >> 1], (uint32_t)(ov[i >> 1] >> 32));
#pragma unroll
        for (int mt = 0; mt < 2; mt++)
#pragma unroll
            for (int i = 0; i < 4; i++)
                asm volatile("st.shared.f32 [%0], %1;" ::"r"(rw + (16 * mt + 36 * (i & 1) + 8 * (i >> 1)) * 4),
                             "f"(((i & 1) ? g1 : g0) * (acc[mt][0][i] + acc[mt][1][i]) + ((i & 1) ? m1 : m0) * acm[mt][i]) : "memory");
        cons_sync();
        float u[8];
#pragma unroll
        for (int w = 0; w < 8; w++) asm volatile("ld.shared.f32 %0, [%1];" : "=f"(u[w]) : "r"(rr + w * 8 * 36 * 4) : "memory");
        const float v = ((u[0] + u[1]) + (u[2] + u[3])) + ((u[4] + u[5]) + (u[6] + u[7]));
        const uint32_t vmax = __reduce_max_sync(~0u, __float_as_uint(v) & 0x7fffffffu);
        unsigned long long add = acc_encode(v, 1);
        const bool boxed = vmax - 0x37800000u >= 0x45000000u - 0x37800000u;
        asm("{\n.reg .pred p;\nsetp.ne.u32 p, %1, 0;\n@p mov.b64 %0, 17;\n}" : "+l"(add) : "r"((uint32_t)boxed));
        unsigned long long tot;
        asm volatile("atom.relaxed.gpu.global.add.u64 %0, [%1], %2;" : "=l"(tot) : "l"(accp), "l"(add) : "memory");
        TLMAX(27);
        if (boxed) st_pkt8(&sc->box[pk * NB * DM + e], __float_as_uint(v), tag);
        tot += add;
        if (((uint32_t)tot & 15u) == 9u) {
            float res = acc_decode(tot);
            if ((uint32_t)tot & 0x1f0u) {
                const uint32_t nbox = ((uint32_t)tot >> 4) & 15u;
                if (nbox == 8u) res = 0.f;
                if (nbox == 8u || ((uint32_t)tot & 256u)) res += misc[8 + warp] * b2v;
                for (unsigned n = 0;; n++) {
                    float sum = 0.f;
                    uint32_t found = 0;
                    for (int k = 0; k < 8; k++) {
                        unsigned long long pv;
                        asm volatile("ld.relaxed.gpu.global.b64 %0, [%1];" : "=l"(pv) : "l"(&sc->box[k * NB * DM + e]) : "memory");
                        if ((uint32_t)(pv >> 32) == tag) { sum += __uint_as_float((uint32_t)pv); found++; }
                    }
                    if (found == nbox) { res += sum; break; }
                    if (n > SPIN_LIMIT) __trap();
                }
            }
            asm volatile("st.global.u16 [%0], %1;" ::"l"(outp), "h"(__bfloat16_as_ushort(__float2bfloat16_rn(res))) : "memory");
            asm volatile("st.global.u64 [%0], 0;" ::"l"(accp) : "memory");
        }
        TLMAX(30);
    }
}

__device__ float g_fq[NB * QD], g_fo[NB * QD], g_fh[NB * FF];

__device__ __forceinline__ float ldf(const __nv_bfloat16* p, size_t i) { return __bfloat162float(p[i]); }

__global__ void fb_qh(const __nv_bfloat16* x, const __nv_bfloat16* wq, const __nv_bfloat16* w1, const __nv_bfloat16* b1) {
    const int b = blockIdx.y, n = blockIdx.x * 256 + threadIdx.x;
    float a = 0.f;
    if (n < QD) {
        for (int k = 0; k < DM; k++) a += ldf(x, b * DM + k) * ldf(wq, (size_t)k * QD + n);
        g_fq[b * QD + n] = bf16r(a);
        return;
    }
    const int f = n - QD;
    float m = 0.f, v = 0.f;
    for (int k = 0; k < DM; k++) m += ldf(x, b * DM + k);
    m *= 1.f / DM;
    for (int k = 0; k < DM; k++) { const float d = ldf(x, b * DM + k) - m; v += d * d; }
    const float mb = bf16r(m), sd = bf16r(sqrtf(bf16r(bf16r(v * (1.f / DM)) + 1e-5f)));
    for (int k = 0; k < DM; k++) a += bf16r(bf16r(ldf(x, b * DM + k) - mb) / sd) * ldf(w1, (size_t)k * FF + f);
    const float u = bf16r(bf16r(a) + ldf(b1, f));
    g_fh[b * FF + f] = bf16r(u / (1.f + expf(-1.5957691216057308f * (u + 0.044715f * u * u * u))));
}
__global__ void fb_attn(const __nv_bfloat16* kc, const __nv_bfloat16* vc) {
    __shared__ float sc[WIN];
    const int h = blockIdx.x, b = blockIdx.y, tid = threadIdx.x, lane = tid & 31;
    const size_t base = ((size_t)(b * 8 + h / 2) * SK + (SK - WIN)) * 256;
    for (int k = tid >> 5; k < WIN; k += 8) {
        float a = 0.f;
        for (int d = lane; d < 256; d += 32) a += g_fq[b * QD + h * 256 + d] * ldf(kc, base + (size_t)k * 256 + d);
        for (int o = 16; o; o >>= 1) a += __shfl_xor_sync(~0u, a, o);
        if (lane == 0) sc[k] = bf16r(a) * 0.0625f;
    }
    __syncthreads();
    float m = sc[0], l = 0.f, a = 0.f;
    for (int k = 1; k < WIN; k++) m = fmaxf(m, sc[k]);
    for (int k = 0; k < WIN; k++) l += expf(sc[k] - m);
    for (int k = 0; k < WIN; k++) a += bf16r(expf(sc[k] - m) / l) * ldf(vc, base + (size_t)k * 256 + tid);
    g_fo[b * QD + h * 256 + tid] = bf16r(a);
}
__global__ void fb_out(const __nv_bfloat16* x, const __nv_bfloat16* gw, const __nv_bfloat16* wo, const __nv_bfloat16* w2,
                       const __nv_bfloat16* b2, __nv_bfloat16* out) {
    const int b = blockIdx.y, n = blockIdx.x * 64 + threadIdx.x;
    float gs = 0.f, a = 0.f, c = 0.f;
    for (int k = 0; k < DM; k++) gs += bf16r(ldf(x, b * DM + k) * ldf(gw, k));
    const float gt = bf16r(1.f / (1.f + expf(-bf16r(gs))));
    for (int k = 0; k < QD; k++) a += g_fo[b * QD + k] * ldf(wo, (size_t)k * DM + n);
    for (int k = 0; k < FF; k++) c += g_fh[b * FF + k] * ldf(w2, (size_t)k * DM + n);
    out[b * DM + n] = __float2bfloat16_rn(gt * a + bf16r(1.f - gt) * (c + ldf(b2, n)));
}

typedef CUresult (*EncodeFn)(CUtensorMap*, CUtensorMapDataType, cuuint32_t, void*, const cuuint64_t*, const cuuint64_t*,
                             const cuuint32_t*, const cuuint32_t*, CUtensorMapInterleave, CUtensorMapSwizzle,
                             CUtensorMapL2promotion, CUtensorMapFloatOOBfill);

bool make_map(EncodeFn encode, CUtensorMap* tm, void* base, int rank, const cuuint64_t* dims, const cuuint64_t* strides,
              const cuuint32_t* box, CUtensorMapSwizzle sw, CUtensorMapL2promotion promo) {
    const cuuint32_t es[3] = {1, 1, 1};
    return encode(tm, CU_TENSOR_MAP_DATA_TYPE_BFLOAT16, rank, base, dims, strides, box, es, CU_TENSOR_MAP_INTERLEAVE_NONE, sw,
                  promo, CU_TENSOR_MAP_FLOAT_OOB_FILL_NONE) == CUDA_SUCCESS;
}

}

extern "C" void kernel_launch(void* const* d_in, const int* in_sizes, int n_in, void* d_out, int out_size) {
    (void)in_sizes; (void)n_in; (void)out_size;
    typedef const __nv_bfloat16* cbf;
    static bool init = false, fused = false;
    static EncodeFn encode = nullptr;
    static Scratch* scratch = nullptr;
    static int tau = 0;
    if (!init) {
        init = true;
        void* fn = nullptr;
        cudaDriverEntryPointQueryResult qr;
        cudaGetDriverEntryPoint("cuTensorMapEncodeTiled", &fn, cudaEnableDefault, &qr);
        encode = (EncodeFn)fn;
        cudaGetSymbolAddress((void**)&scratch, g_scratch);
        int dev = 0, khz = 0, bits = 0, clusters = 0;
        cudaGetDevice(&dev);
        cudaDeviceGetAttribute(&khz, cudaDevAttrMemoryClockRate, dev);
        cudaDeviceGetAttribute(&bits, cudaDevAttrGlobalMemoryBusWidth, dev);
        const double peak = 2.0 * khz * 1e-6 * bits / 8.0;
        tau = peak > 0 ? (int)(NCTA * (double)STAGE_BYTES / (PACE_FRAC * peak) + 0.5) : 0;
        if (cudaFuncSetAttribute(fused_kernel, cudaFuncAttributeMaxDynamicSharedMemorySize, SMEM_BYTES) == cudaSuccess) {
            cudaLaunchConfig_t cfg = {};
            cfg.gridDim = dim3(NCTA); cfg.blockDim = dim3(NTHREADS); cfg.dynamicSmemBytes = SMEM_BYTES;
            cudaLaunchAttribute at;
            at.id = cudaLaunchAttributeClusterDimension;
            at.val.clusterDim.x = 2; at.val.clusterDim.y = 1; at.val.clusterDim.z = 1;
            cfg.attrs = &at; cfg.numAttrs = 1;
            if (cudaOccupancyMaxActiveClusters(&clusters, fused_kernel, &cfg) != cudaSuccess) clusters = 0;
        }
        fused = encode && scratch && clusters >= NCTA / 2;
        (void)cudaGetLastError();
    }
    CUtensorMap tmK, tmV, tmWo, tmW2, tmWq, tmW1;
    bool ok = fused;
    if (ok) {
        const cuuint64_t dimsKV[3] = {64, (cuuint64_t)64 * SK, 4}, strKV[2] = {512, 128};
        const cuuint32_t boxK[3] = {64, 32, 4}, boxV[3] = {64, 64, 2};
        const cuuint64_t dimsO[2] = {DM, QD}, dims2[2] = {DM, FF}, strO[1] = {DM * 2};
        const cuuint32_t boxO[2] = {32, 256}, box2[2] = {32, 224};
        const cuuint64_t dimsQ[2] = {QD, DM}, dims1[2] = {FF, DM}, strQ[1] = {QD * 2}, str1[1] = {FF * 2};
        const cuuint32_t boxQ[2] = {32, 256}, box1[2] = {16, 256};
        ok = make_map(encode, &tmK, d_in[1], 3, dimsKV, strKV, boxK, CU_TENSOR_MAP_SWIZZLE_128B, CU_TENSOR_MAP_L2_PROMOTION_L2_256B) &&
             make_map(encode, &tmV, d_in[2], 3, dimsKV, strKV, boxV, CU_TENSOR_MAP_SWIZZLE_128B, CU_TENSOR_MAP_L2_PROMOTION_L2_256B) &&
             make_map(encode, &tmWo, d_in[4], 2, dimsO, strO, boxO, CU_TENSOR_MAP_SWIZZLE_64B, CU_TENSOR_MAP_L2_PROMOTION_NONE) &&
             make_map(encode, &tmW2, d_in[8], 2, dims2, strO, box2, CU_TENSOR_MAP_SWIZZLE_64B, CU_TENSOR_MAP_L2_PROMOTION_NONE) &&
             make_map(encode, &tmWq, d_in[3], 2, dimsQ, strQ, boxQ, CU_TENSOR_MAP_SWIZZLE_64B, CU_TENSOR_MAP_L2_PROMOTION_NONE) &&
             make_map(encode, &tmW1, d_in[6], 2, dims1, str1, box1, CU_TENSOR_MAP_SWIZZLE_32B, CU_TENSOR_MAP_L2_PROMOTION_NONE);
    }
    if (!ok) {
        fb_qh<<<dim3((QD + FF) / 256, NB), 256>>>((cbf)d_in[0], (cbf)d_in[3], (cbf)d_in[6], (cbf)d_in[7]);
        fb_attn<<<dim3(16, NB), 256>>>((cbf)d_in[1], (cbf)d_in[2]);
        fb_out<<<dim3(DM / 64, NB), 64>>>((cbf)d_in[0], (cbf)d_in[10], (cbf)d_in[4], (cbf)d_in[8], (cbf)d_in[9], (__nv_bfloat16*)d_out);
        return;
    }
    Params P;
    P.sc = scratch;
    P.wq = (cbf)d_in[3]; P.x = (cbf)d_in[0]; P.gate_w = (cbf)d_in[10]; P.b1 = (cbf)d_in[7]; P.b2 = (cbf)d_in[9];
    P.out = (__nv_bfloat16*)d_out;
    P.tau = tau;
    P.lead = (int)(PACE_LEAD * tau);
    P.gate = (int)(PACE_GATE * P.tau) - P.lead;
    P.a16 = PACE_GAIN16;
    P.target = (int)(PACE_BACKLOG * P.tau);
    fused_kernel<<<NCTA, NTHREADS, SMEM_BYTES>>>(P, tmWq, tmK, tmV, tmW1, tmW2, tmWo);
}
```

```cpp
#include <cuda_runtime.h>
#include <cuda_bf16.h>
#include <cuda.h>
#include <stdint.h>

namespace {

constexpr int NB = 8, DM = 448, SK = 4096, WIN = 1024, FF = 1792, QD = 4096;
constexpr int NCTA = 128, NPROJ = 112;
constexpr int NSTAGE = 12, STAGE_BYTES = 16384;
constexpr int WINDOW = 6;
constexpr int NEARLY = 3;
constexpr int MTILE = 23, RTILE = 28;
constexpr int HPOS = 11;
constexpr double PACE_FRAC = 0.9255;
constexpr double PACE_LEAD = 2.78;
constexpr double PACE_BACKLOG = 3.32;
constexpr int PACE_GAIN16 = 21;
constexpr double PACE_GATE = 38.03;
constexpr int NTHREADS = 320;

constexpr int OFF_SC = NSTAGE * STAGE_BYTES;
constexpr int OFF_RED = OFF_SC + 9216;
constexpr int OFF_PF = OFF_RED;
constexpr int OFF_Q = OFF_RED + 8192;
constexpr int OFF_MISC = OFF_Q + 1024;
constexpr int OFF_T0 = OFF_MISC + 240, OFF_SHIFT = OFF_MISC + 244;
constexpr int OFF_BAR = OFF_MISC + 256;
constexpr int SMEM_USED = OFF_BAR + 256;
constexpr int SMEM_BYTES = SMEM_USED + 1024;

constexpr unsigned SPIN_LIMIT = 1u << 22;
constexpr unsigned TIME_LIMIT = 1u << 12;

struct __align__(256) Scratch {
    uint4 o[16 * 16 * 32];
    uint4 h[NPROJ * 32];
    uint2 q[NB * 2048];
    uint2 box[8 * NB * DM];
    unsigned long long acc[NB * DM];
    unsigned epoch[NCTA];
    unsigned late[2][32];
};
__device__ Scratch g_scratch;

struct Params {
    Scratch* sc;
    const __nv_bfloat16 *wq, *x, *gate_w, *b1, *b2;
    __nv_bfloat16* out;
    int tau, lead, gate, a16, target;
};

__device__ __forceinline__ uint32_t smem_u32(const void* p) { return (uint32_t)__cvta_generic_to_shared(p); }
__device__ __forceinline__ void mbar_init(uint32_t bar, int cnt) {
    asm volatile("mbarrier.init.shared::cta.b64 [%0], %1;" ::"r"(bar), "r"(cnt) : "memory");
}
__device__ __forceinline__ void mbar_expect_tx(uint32_t bar, uint32_t bytes) {
    asm volatile("mbarrier.arrive.expect_tx.shared::cta.b64 _, [%0], %1;" ::"r"(bar), "r"(bytes) : "memory");
}
__device__ __forceinline__ void mbar_arrive(uint32_t bar) {
    asm volatile("mbarrier.arrive.shared::cta.b64 _, [%0];" ::"r"(bar) : "memory");
}
__device__ __forceinline__ void mbar_arrive_n(uint32_t bar, uint32_t n) {
    asm volatile("mbarrier.arrive.shared::cta.b64 _, [%0], %1;" ::"r"(bar), "r"(n) : "memory");
}
__device__ __forceinline__ void st_async2(uint32_t addr, float a, float b, uint32_t bar) {
    asm volatile("st.async.weak.shared::cluster.mbarrier::complete_tx::bytes.v2.f32 [%0], {%1, %2}, [%3];"
                 ::"r"(addr), "f"(a), "f"(b), "r"(bar) : "memory");
}
__device__ __forceinline__ void mbar_wait(uint32_t bar, uint32_t parity) {
    uint32_t done;
    unsigned n = 0;
    do {
        asm volatile("{\n.reg .pred p;\nmbarrier.try_wait.parity.shared::cta.b64 p, [%1], %2;\nselp.u32 %0, 1, 0, p;\n}"
                     : "=r"(done) : "r"(bar), "r"(parity) : "memory");
        if (++n > SPIN_LIMIT) __trap();
    } while (!done);
}
__device__ __forceinline__ void tma2d(uint32_t dst, const CUtensorMap* tm, int c0, int c1, uint32_t bar, uint64_t pol) {
    asm volatile("cp.async.bulk.tensor.2d.shared::cluster.global.mbarrier::complete_tx::bytes.L2::cache_hint [%0], [%1, {%3, %4}], [%2], %5;"
                 ::"r"(dst), "l"(tm), "r"(bar), "r"(c0), "r"(c1), "l"(pol) : "memory");
}
__device__ __forceinline__ void tma3d(uint32_t dst, const CUtensorMap* tm, int c0, int c1, int c2, uint32_t bar, uint64_t pol) {
    asm volatile("cp.async.bulk.tensor.3d.shared::cluster.global.mbarrier::complete_tx::bytes.L2::cache_hint [%0], [%1, {%3, %4, %5}], [%2], %6;"
                 ::"r"(dst), "l"(tm), "r"(bar), "r"(c0), "r"(c1), "r"(c2), "l"(pol) : "memory");
}
__device__ __forceinline__ void ldsm4(uint32_t (&r)[4], uint32_t addr) {
    asm volatile("ldmatrix.sync.aligned.m8n8.x4.shared.b16 {%0,%1,%2,%3}, [%4];"
                 : "=r"(r[0]), "=r"(r[1]), "=r"(r[2]), "=r"(r[3]) : "r"(addr) : "memory");
}
__device__ __forceinline__ void ldsm4t(uint32_t (&r)[4], uint32_t addr) {
    asm volatile("ldmatrix.sync.aligned.m8n8.x4.trans.shared.b16 {%0,%1,%2,%3}, [%4];"
                 : "=r"(r[0]), "=r"(r[1]), "=r"(r[2]), "=r"(r[3]) : "r"(addr) : "memory");
}
__device__ __forceinline__ void mma16816(float (&c)[4], uint32_t a0, uint32_t a1, uint32_t a2, uint32_t a3, uint32_t b0, uint32_t b1) {
    asm volatile("mma.sync.aligned.m16n8k16.row.col.f32.bf16.bf16.f32 {%0,%1,%2,%3}, {%4,%5,%6,%7}, {%8,%9}, {%0,%1,%2,%3};"
                 : "+f"(c[0]), "+f"(c[1]), "+f"(c[2]), "+f"(c[3])
                 : "r"(a0), "r"(a1), "r"(a2), "r"(a3), "r"(b0), "r"(b1));
}
__device__ __forceinline__ void cons_sync() { asm volatile("bar.sync 1, 256;" ::: "memory"); }

__device__ __forceinline__ float bf16r(float v) { return __bfloat162float(__float2bfloat16_rn(v)); }
__device__ __forceinline__ uint32_t pack_bf16(float lo, float hi) {
    uint32_t r;
    asm("cvt.rn.bf16x2.f32 %0, %1, %2;" : "=r"(r) : "f"(hi), "f"(lo));
    return r;
}
__device__ __forceinline__ float bf_lo(uint32_t w) { return __uint_as_float(w << 16); }
__device__ __forceinline__ float bf_hi(uint32_t w) { return __uint_as_float(w & 0xffff0000u); }

__device__ __forceinline__ void st_pkt8(uint2* p, uint32_t d, uint32_t tag) {
    unsigned long long v = ((unsigned long long)tag << 32) | d;
    asm volatile("st.relaxed.gpu.global.b64 [%0], %1;" ::"l"(p), "l"(v) : "memory");
}
__device__ __forceinline__ uint32_t poll_pkt8(const uint2* p, uint32_t tag) {
    unsigned long long v;
    for (unsigned n = 0;; n++) {
        asm volatile("ld.relaxed.gpu.global.b64 %0, [%1];" : "=l"(v) : "l"(p) : "memory");
        if ((uint32_t)(v >> 32) == tag) break;
        if (n > SPIN_LIMIT) __trap();
    }
    return (uint32_t)v;
}
__device__ __forceinline__ void st_pkt16(uint4* p, uint32_t d0, uint32_t d1, uint32_t tag) {
    unsigned long long lo = ((unsigned long long)d1 << 32) | d0, hi = tag;
    asm volatile("{\n.reg .b128 t;\nmov.b128 t, {%1, %2};\nst.relaxed.gpu.global.b128 [%0], t;\n}" ::"l"(p), "l"(lo), "l"(hi) : "memory");
}
__device__ __forceinline__ void ld_pkt16(const uint4* p, unsigned long long& lo, unsigned long long& hi) {
    asm volatile("{\n.reg .b128 t;\nld.relaxed.gpu.global.b128 t, [%2];\nmov.b128 {%0, %1}, t;\n}" : "=l"(lo), "=l"(hi) : "l"(p) : "memory");
}
__device__ __forceinline__ void reld_pkt16(const uint4* p, unsigned long long& lo, unsigned long long& hi, bool need) {
    asm volatile("{\n.reg .b128 t;\n.reg .pred p;\nsetp.ne.u32 p, %3, 0;\nmov.b128 t, {%0, %1};\n@p ld.relaxed.gpu.global.b128 t, [%2];\nmov.b128 {%0, %1}, t;\n}"
                 : "+l"(lo), "+l"(hi) : "l"(p), "r"((uint32_t)need) : "memory");
}
__device__ __forceinline__ bool mbar_test(uint32_t bar, uint32_t parity) {
    uint32_t done;
    asm volatile("{\n.reg .pred p;\nmbarrier.test_wait.parity.shared::cta.b64 p, [%1], %2;\nselp.u32 %0, 1, 0, p;\n}"
                 : "=r"(done) : "r"(bar), "r"(parity) : "memory");
    return done;
}
__device__ __forceinline__ uint32_t pin(uint32_t v) { return __shfl_sync(~0u, v, threadIdx.x & 31); }
template <class T>
__device__ __forceinline__ T* pin(T* p) {
    return reinterpret_cast<T*>(__shfl_sync(~0u, reinterpret_cast<unsigned long long>(p), threadIdx.x & 31));
}
template <int N, int S>
__device__ __forceinline__ void gather_pkts(const uint4* p, uint32_t tag, unsigned long long (&lo)[N]) {
    unsigned long long hi[N];
#pragma unroll
    for (int i = 0; i < N; i++) ld_pkt16(p + 32 * (i & 1) + S * (i >> 1), lo[i], hi[i]);
    for (unsigned n = 0;; n++) {
        bool need[N], any = false;
#pragma unroll
        for (int i = 0; i < N; i++) { need[i] = (uint32_t)hi[i] != tag; any |= need[i]; }
        if (!__any_sync(~0u, any)) break;
#pragma unroll
        for (int i = 0; i < N; i++) reld_pkt16(p + 32 * (i & 1) + S * (i >> 1), lo[i], hi[i], need[i]);
        if (n > SPIN_LIMIT) __trap();
    }
}
__device__ __forceinline__ unsigned long long acc_encode(float v, int flags) {
    const float th = __fadd_rn(v, 12288.f);
    const float tl = __fadd_rn(__fsub_rn(v, __fsub_rn(th, 12288.f)), 0.0029296875f);
    const int hi = __float_as_int(th) - 0x46400000, lo = __float_as_int(tl) - 0x3b400000;
    return (unsigned long long)((long long)lo * 65536 + flags) + ((unsigned long long)(uint32_t)(hi << 6) << 32);
}
__device__ __forceinline__ float acc_decode(unsigned long long tot) {
    return fmaf((float)(int)(tot >> 32), 0x1p-16f, (float)((uint32_t)tot >> 16) * 0x1p-32f);
}

__global__ void __cluster_dims__(2, 1, 1) __launch_bounds__(NTHREADS, 1)
fused_kernel(const __grid_constant__ Params P, const __grid_constant__ CUtensorMap tmWq,
             const __grid_constant__ CUtensorMap tmK, const __grid_constant__ CUtensorMap tmV,
             const __grid_constant__ CUtensorMap tmW1, const __grid_constant__ CUtensorMap tmW2,
             const __grid_constant__ CUtensorMap tmWo) {
    extern __shared__ unsigned char smem_raw[];
    const uint32_t raw = smem_u32(smem_raw);
    const uint32_t sb = (raw + 1023u) & ~1023u;
    unsigned char* sp = smem_raw + (sb - raw);

    const int tid = threadIdx.x, warp = tid >> 5, lane = tid & 31;
    const int g = lane >> 2, t = lane & 3;
    const int j = blockIdx.x;
    const int hkv = j >> 4, bb = (j >> 1) & 7, s = j & 1;
    const bool proj = j < NPROJ;
    const int pk = j / 14, pc = j - pk * 14;

    const uint32_t bar_full = sb + OFF_BAR, bar_empty = bar_full + 8 * NSTAGE, bar_sc = bar_empty + 8 * NSTAGE;

    if (warp == 9) {
        const uint32_t ep = *reinterpret_cast<volatile unsigned*>(&P.sc->epoch[j]);
        if (lane == 0) asm volatile("st.shared.u32 [%0], %1;" ::"r"(sb + OFF_MISC + 248), "r"(ep) : "memory");
        asm volatile("barrier.cluster.arrive.relaxed.aligned;" ::: "memory");
        asm volatile("barrier.cluster.wait.acquire.aligned;" ::: "memory");
        if (lane == 0) {
            unsigned* slot = &P.sc->late[ep & 1][0];
            if (j == 0) P.sc->late[(ep ^ 1) & 1][0] = 0;
            mbar_wait(bar_full + 8 * (MTILE % NSTAGE), ((MTILE / NSTAGE) & 1) ^ 1);
            mbar_wait(bar_full + 8 * (MTILE % NSTAGE), (MTILE / NSTAGE) & 1);
            uint32_t now, t0, v;
            asm volatile("mov.u32 %0, %%globaltimer_lo;" : "=r"(now));
            asm volatile("ld.volatile.shared.u32 %0, [%1];" : "=r"(t0) : "r"(sb + OFF_T0) : "memory");
            const int lat = min(max((int)(now - t0) - (MTILE * P.tau - P.lead), 0), 6000);
            asm volatile("red.relaxed.gpu.global.add.u32 [%0], %1;" ::"l"(slot), "r"((1u << 20) + lat) : "memory");
            for (unsigned n = 0; n < TIME_LIMIT; n++) {
                __nanosleep(100);
                asm volatile("mov.u32 %0, %%globaltimer_lo;" : "=r"(now));
                if ((int)(now - t0) >= RTILE * P.tau - P.lead) break;
            }
            asm volatile("ld.relaxed.gpu.global.u32 %0, [%1];" : "=r"(v) : "l"(slot) : "memory");
            const int mean = ((int)(v & 0xfffffu) + (NCTA - (int)(v >> 20)) * (RTILE - MTILE) * P.tau) / NCTA;
            const int shift = min(max(((mean - P.target) * P.a16) >> 4, -P.tau), 3 * P.tau);
            asm volatile("st.volatile.shared.u32 [%0], %1;" ::"r"(sb + OFF_SHIFT), "r"(shift) : "memory");
        }
        return;
    }
    if (warp == 8) {
        int tau = P.tau, lead = P.lead;
        uint64_t pol;
        asm volatile("createpolicy.fractional.L2::evict_first.b64 %0, 1.0;" : "=l"(pol));
        const int row0 = (bb * 8 + hkv) * SK + (SK - WIN);
        if (lane == 0) {
#pragma unroll
            for (int i = 0; i < NEARLY; i++) mbar_init(bar_full + 8 * i, 1);
            asm volatile("fence.proxy.async.shared::cta;" ::: "memory");
            mbar_expect_tx(bar_full, STAGE_BYTES);
            tma2d(sb, &tmWq, 32 * j, 0, bar_full, pol);
            mbar_expect_tx(bar_full + 8, STAGE_BYTES);
            tma2d(sb + STAGE_BYTES, &tmWq, 32 * j, 256, bar_full + 8, pol);
#pragma unroll
            for (int i = 2; i < NEARLY; i++) {
                mbar_expect_tx(bar_full + 8 * i, STAGE_BYTES);
                tma3d(sb + i * STAGE_BYTES, &tmK, 0, row0 + s * 512 + (i - 2) * 32, 0, bar_full + 8 * i, pol);
            }
            asm volatile("prefetch.tensormap [%0];" ::"l"(&tmK) : "memory");
            asm volatile("prefetch.tensormap [%0];" ::"l"(&tmV) : "memory");
            asm volatile("prefetch.tensormap [%0];" ::"l"(&tmW1) : "memory");
            asm volatile("prefetch.tensormap [%0];" ::"l"(&tmW2) : "memory");
            asm volatile("prefetch.tensormap [%0];" ::"l"(&tmWo) : "memory");
#pragma unroll
            for (int i = NEARLY; i < NSTAGE; i++) mbar_init(bar_full + 8 * i, 1);
#pragma unroll
            for (int i = 0; i < NSTAGE; i++) mbar_init(bar_empty + 8 * i, 8);
            mbar_init(bar_sc, 1);
            asm volatile("fence.mbarrier_init.release.cluster;" ::: "memory");
            asm volatile("fence.proxy.async.shared::cta;" ::: "memory");
        }
        __syncwarp();
        asm volatile("barrier.cluster.arrive.relaxed.aligned;" ::: "memory");
        if (lane == 0) {
            uint32_t t0;
            asm volatile("mov.u32 %0, %%globaltimer_lo;" : "=r"(t0));
            asm volatile("st.shared.v2.u32 [%0], {%1, 0};" ::"r"(sb + OFF_T0), "r"(t0) : "memory");
            mbar_expect_tx(bar_sc, 8192);
            const int ntiles = proj ? 38 : 35;
            int st = NEARLY, par = 1, wst = 0, wpar = 0, arrived = 0;
            for (int i = NEARLY; i < ntiles; i++) {
                while (arrived <= i - WINDOW) {
                    mbar_wait(bar_full + 8 * wst, wpar);
                    if (++wst == NSTAGE) { wst = 0; wpar ^= 1; }
                    arrived++;
                }
                if (i >= NSTAGE) mbar_wait(bar_empty + 8 * st, par);
                {
                    const int due = i * tau - lead;
                    uint32_t now;
                    int shift = 0;
                    unsigned n = 0;
                    do {
                        if (i > RTILE) asm volatile("ld.volatile.shared.u32 %0, [%1];" : "=r"(shift) : "r"(sb + OFF_SHIFT) : "memory");
                        asm volatile("mov.u32 %0, %%globaltimer_lo;" : "=r"(now));
                    } while ((int)(now - t0) < due + shift && ++n < TIME_LIMIT);
                }
                const uint32_t dst = sb + st * STAGE_BYTES, bar = bar_full + 8 * st;
                if (i == 18) {
                    if (proj) {
                        mbar_expect_tx(bar, STAGE_BYTES);
                        tma2d(dst, &tmW1, 16 * j, 0, bar, pol);
                        tma2d(dst + 8192, &tmW1, 16 * j, 256, bar, pol);
                    } else {
                        mbar_arrive(bar);
                    }
                } else {
                    mbar_expect_tx(bar, i == 35 ? 224 * 64 : STAGE_BYTES);
                    if (i < 35) {
                        const bool isk = i < 18;
                        tma3d(dst, isk ? &tmK : &tmV, 0, isk ? row0 + s * 512 + (i - 2) * 32 : row0 + (i - 19) * 64, isk ? 0 : 2 * s, bar, pol);
                    } else {
                        tma2d(dst, i == 35 ? &tmW2 : &tmWo, pc * 32, i == 35 ? pk * 224 : pk * 512 + (i - 36) * 256, bar, pol);
                    }
                }
                if (++st == NSTAGE) { st = 0; par ^= 1; }
            }
        }
        __syncwarp();
        asm volatile("barrier.cluster.wait.acquire.aligned;" ::: "memory");
        return;
    }

    Scratch* sc = P.sc;
    const __nv_bfloat16 *x = P.x, *gate_w = P.gate_w, *b1 = P.b1, *b2 = P.b2;
    __nv_bfloat16* out = P.out;
    if (tid == 224) asm volatile("st.shared.u32 [%0], %1;" ::"r"(sb + OFF_MISC + 252), "r"(P.tau) : "memory");
    if (lane == 0 && warp < 2)
        asm volatile("cp.async.bulk.prefetch.L2.global [%0], %1;"
                     ::"l"(reinterpret_cast<const char*>(P.wq) + (size_t)j * 28672 + warp * 14336), "r"(14336) : "memory");
    uint2* q_slot = &sc->q[(tid >> 4) * 2048 + 16 * j + (tid & 15)];
    if (tid < 128) st_pkt8(q_slot, 0u, 0u);
    uint4* o_slot = &sc->o[(((2 * hkv + (g & 1)) * 16 + s * 8 + warp) * 8 + bb) * 4 + (g >> 1)];
    if (t == 0) st_pkt16(o_slot, 0u, 0u, 0u);
    uint32_t tag = *reinterpret_cast<volatile unsigned*>(&sc->epoch[j]);
    uint32_t xb[8];
    {
        const uint32_t* xp = reinterpret_cast<const uint32_t*>(x + g * DM) + (warp < 7 ? warp : 0) * 32 + t;
#pragma unroll
        for (int i = 0; i < 8; i++) xb[i] = __ldg(xp + 4 * i);
    }
    uint32_t xw[7], gw[7];
#pragma unroll
    for (int i = 0; i < 7; i++) {
        xw[i] = __ldg(reinterpret_cast<const uint32_t*>(x + warp * DM) + lane + 32 * i);
        gw[i] = __ldg(reinterpret_cast<const uint32_t*>(gate_w) + lane + 32 * i);
    }
    uint32_t b1w = 0;
    float b2v = 0.f;
    if (proj) {
        b1w = __ldg(reinterpret_cast<const uint32_t*>(b1 + 16 * j) + (tid & 7));
        b2v = __bfloat162float(b2[pc * 32 + lane]);
    }
    asm volatile("barrier.cluster.arrive.relaxed.aligned;" ::: "memory");
    asm volatile("barrier.cluster.wait.acquire.aligned;" ::: "memory");
    float* misc = reinterpret_cast<float*>(sp + OFF_MISC);
    float* red = reinterpret_cast<float*>(sp + OFF_RED);
    const int r = lane & 7, mi = lane >> 3;
    if (warp < 7) {
        float c[2][4] = {};
        const int row = warp * 64 + r + 8 * (mi >> 1);
        const uint32_t qa0 = sb + row * 64 + (((mi & 1) ^ ((r >> 1) & 3)) << 4);
        const uint32_t qa1 = sb + row * 64 + (((2 + (mi & 1)) ^ ((r >> 1) & 3)) << 4);
        mbar_wait(bar_full + 8 * (warp >> 2), 0);
#pragma unroll
        for (int ks = 0; ks < 4; ks++) {
            uint32_t a0[4], a1[4];
            ldsm4t(a0, qa0 + ks * 1024);
            ldsm4t(a1, qa1 + ks * 1024);
            mma16816(c[0], a0[0], a0[1], a0[2], a0[3], xb[2 * ks], xb[2 * ks + 1]);
            mma16816(c[1], a1[0], a1[1], a1[2], a1[3], xb[2 * ks], xb[2 * ks + 1]);
        }
        float* r0 = red + (warp * 8 + 2 * t) * 36 + g;
#pragma unroll
        for (int mt = 0; mt < 2; mt++) {
            r0[16 * mt] = c[mt][0];
            r0[36 + 16 * mt] = c[mt][1];
            r0[16 * mt + 8] = c[mt][2];
            r0[36 + 16 * mt + 8] = c[mt][3];
        }
    }
    cons_sync();
    tag = tag + 1u == 0u ? 2u : tag + 1u;
    if (tid < 128) {
        float v0 = 0.f, v1 = 0.f;
#pragma unroll
        for (int w = 0; w < 7; w++) {
            const float2 v = *reinterpret_cast<const float2*>(red + (w * 8 + (tid >> 4)) * 36 + 2 * (tid & 15));
            v0 += v.x; v1 += v.y;
        }
        st_pkt8(q_slot, pack_bf16(v0, v1), tag);
    } else if (tid >= 224 && tid < 226) {
        mbar_arrive_n(bar_empty + 8 * (tid - 224), 8);
    }
    {
        float sum = 0.f, gs = 0.f;
#pragma unroll
        for (int i = 0; i < 7; i++) {
            sum += bf_lo(xw[i]) + bf_hi(xw[i]);
            gs += bf16r(bf_lo(xw[i]) * bf_lo(gw[i])) + bf16r(bf_hi(xw[i]) * bf_hi(gw[i]));
        }
#pragma unroll
        for (int o = 16; o; o >>= 1) { sum += __shfl_xor_sync(~0u, sum, o); gs += __shfl_xor_sync(~0u, gs, o); }
        const float mean = sum * (1.f / DM);
        float vs = 0.f;
#pragma unroll
        for (int i = 0; i < 7; i++) {
            const float d0 = bf_lo(xw[i]) - mean, d1 = bf_hi(xw[i]) - mean;
            vs += d0 * d0 + d1 * d1;
        }
#pragma unroll
        for (int o = 16; o; o >>= 1) vs += __shfl_xor_sync(~0u, vs, o);
        if (lane == 0) {
            const float gt = bf16r(__fdividef(1.f, 1.f + __expf(-bf16r(gs))));
            misc[warp] = gt;
            misc[8 + warp] = bf16r(1.f - gt);
            misc[32 + warp] = bf16r(mean);
            misc[40 + warp] = bf16r(__fsqrt_rn(bf16r(bf16r(vs * (1.f / DM)) + 1e-5f)));
        }
    }
    reinterpret_cast<uint32_t*>(sp + OFF_Q)[tid] = poll_pkt8(&sc->q[bb * 2048 + hkv * 256 + tid], tag);
    cons_sync();
    if (tid == 0) sc->epoch[j] = tag;

    {
        uint32_t qa[16][2];
        const uint32_t* qs = reinterpret_cast<const uint32_t*>(sp + OFF_Q) + (g & 1) * 128 + t;
#pragma unroll
        for (int ks = 0; ks < 16; ks++) { qa[ks][0] = qs[ks * 8]; qa[ks][1] = qs[ks * 8 + 4]; }
        const uint32_t a_even = ((warp & 3) * 8 + r) * 128 + ((mi ^ r) << 4);
        const uint32_t a_odd = ((warp & 3) * 8 + r) * 128 + (((mi + 4) ^ r) << 4);
        const uint32_t sc_local = sb + OFF_SC + (g & 1) * 4096 + ((s * 16 + (warp >> 2)) * 4 + t) * 32 + (warp & 3) * 8;
        uint32_t sc_dst, bar_dst;
        asm("mapa.shared::cluster.u32 %0, %1, %2;" : "=r"(sc_dst) : "r"(sc_local), "r"((g >> 1) & 1));
        asm("mapa.shared::cluster.u32 %0, %1, %2;" : "=r"(bar_dst) : "r"(bar_sc), "r"((g >> 1) & 1));
        int st = 2 + (warp >> 2), par = 0;
        for (int i = 0; i < 8; i++) {
            mbar_wait(bar_full + 8 * st, par);
            const uint32_t base = sb + st * STAGE_BYTES;
            float ca[4] = {}, cb[4] = {}, cc[4] = {}, cd[4] = {};
#pragma unroll
            for (int c = 0; c < 4; c++) {
                uint32_t k0[4], k1[4];
                ldsm4(k0, base + c * 4096 + a_even);
                ldsm4(k1, base + c * 4096 + a_odd);
                mma16816(ca, qa[4 * c][0], qa[4 * c][0], qa[4 * c][1], qa[4 * c][1], k0[0], k0[1]);
                mma16816(cb, qa[4 * c + 1][0], qa[4 * c + 1][0], qa[4 * c + 1][1], qa[4 * c + 1][1], k0[2], k0[3]);
                mma16816(cc, qa[4 * c + 2][0], qa[4 * c + 2][0], qa[4 * c + 2][1], qa[4 * c + 2][1], k1[0], k1[1]);
                mma16816(cd, qa[4 * c + 3][0], qa[4 * c + 3][0], qa[4 * c + 3][1], qa[4 * c + 3][1], k1[2], k1[3]);
            }
            __syncwarp();
            if (lane == 0) mbar_arrive_n(bar_empty + 8 * st, 2);
            if (g < 4) {
                const float s0 = bf16r((ca[0] + cb[0]) + (cc[0] + cd[0])) * 0.0625f;
                const float s1 = bf16r((ca[1] + cb[1]) + (cc[1] + cd[1])) * 0.0625f;
                st_async2(sc_dst + i * 256, s0, s1, bar_dst);
            }
            st += 2;
            if (st >= NSTAGE) { st -= NSTAGE; par ^= 1; }
        }
    }
    if (proj && warp == 4) {
        const float bv = misc[8 + pk] * b2v;
        const bool fits = fabsf(bv) < 2048.f;
        asm volatile("red.relaxed.gpu.global.add.u64 [%0], %1;"
                     ::"l"(&sc->acc[pk * DM + pc * 32 + lane]), "l"(acc_encode(fits ? bv : 0.f, fits ? 1 : 257)) : "memory");
    }
    int st = 18 % NSTAGE, par = (18 / NSTAGE) & 1;
    {
        if (proj || tid == 224) mbar_wait(bar_full + 8 * st, par);
        if (proj) {
            if (warp < 7) {
                const float mb = misc[32 + g], sd = misc[40 + g];
                const uint32_t ha = sb + st * STAGE_BYTES + (warp * 64 + r + 8 * (mi >> 1)) * 32 + (((mi & 1) ^ (r >> 2)) << 4);
                float c[4] = {};
#pragma unroll
                for (int ks = 0; ks < 4; ks++) {
                    uint32_t a2[4], y[2];
                    ldsm4t(a2, ha + ks * 512);
#pragma unroll
                    for (int i = 0; i < 2; i++)
                        y[i] = pack_bf16(__fdividef(bf16r(bf_lo(xb[2 * ks + i]) - mb), sd), __fdividef(bf16r(bf_hi(xb[2 * ks + i]) - mb), sd));
                    mma16816(c, a2[0], a2[1], a2[2], a2[3], y[0], y[1]);
                }
                float* r0 = red + (warp * 8 + 2 * t) * 36 + g;
                r0[0] = c[0]; r0[36] = c[1]; r0[8] = c[2]; r0[44] = c[3];
            }
            cons_sync();
            if (tid < 64) {
                const int b = tid >> 3, cp = tid & 7;
                float v[2] = {0.f, 0.f};
#pragma unroll
                for (int w = 0; w < 7; w++) {
                    const float2 u = *reinterpret_cast<const float2*>(red + (w * 8 + b) * 36 + 2 * cp);
                    v[0] += u.x; v[1] += u.y;
                }
                v[0] = bf16r(bf16r(v[0]) + bf_lo(b1w));
                v[1] = bf16r(bf16r(v[1]) + bf_hi(b1w));
#pragma unroll
                for (int i = 0; i < 2; i++) {
                    const float u = v[i];
                    v[i] = __fdividef(u, 1.f + __expf(-1.5957691216057308f * (u + 0.044715f * u * u * u)));
                }
                const uint32_t w0 = pack_bf16(v[0], v[1]);
                const uint32_t w1w = __shfl_down_sync(~0u, w0, 4);
                if (cp < 4) st_pkt16(&sc->h[j * 32 + b * 4 + cp], w0, w1w, tag);
            }
        }
        if (tid == 224) mbar_arrive_n(bar_empty + 8 * st, 8);
        if (++st == NSTAGE) { st = 0; par ^= 1; }
    }
    mbar_wait(bar_sc, 0);
    {
        const float4* scp = reinterpret_cast<const float4*>(sp + OFF_SC) + tid * 2;
        const float4 u0 = scp[0], u1 = scp[1];
        float e[8] = {u0.x, u0.y, u0.z, u0.w, u1.x, u1.y, u1.z, u1.w};
        float m = e[0];
#pragma unroll
        for (int i = 1; i < 8; i++) m = fmaxf(m, e[i]);
#pragma unroll
        for (int o = 16; o; o >>= 1) m = fmaxf(m, __shfl_xor_sync(~0u, m, o));
        if (lane == 0) misc[16 + warp] = m;
        cons_sync();
        const float4 mm = *reinterpret_cast<const float4*>(misc + 16 + (warp & 4));
        m = fmaxf(fmaxf(mm.x, mm.y), fmaxf(mm.z, mm.w));
        float l = 0.f;
#pragma unroll
        for (int i = 0; i < 8; i++) { e[i] = __expf(e[i] - m); l += e[i]; }
#pragma unroll
        for (int o = 16; o; o >>= 1) l += __shfl_xor_sync(~0u, l, o);
        if (lane == 0) misc[24 + warp] = l;
        cons_sync();
        const float4 ll = *reinterpret_cast<const float4*>(misc + 24 + (warp & 4));
        const float inv = __fdividef(1.f, (ll.x + ll.y) + (ll.z + ll.w));
        reinterpret_cast<uint4*>(sp + OFF_PF)[tid] =
            make_uint4(pack_bf16(e[0] * inv, e[1] * inv), pack_bf16(e[2] * inv, e[3] * inv),
                       pack_bf16(e[4] * inv, e[5] * inv), pack_bf16(e[6] * inv, e[7] * inv));
        cons_sync();
    }
    unsigned long long hv[2] = {0ull, 0ull};
    const uint32_t trow = (r + 8 * (mi >> 1)) * 128;
    {
        float ca[4] = {}, cb[4] = {};
        const uint32_t va = (warp >> 2) * 8192 + trow + (((2 * (warp & 3) + (mi & 1)) ^ r) << 4);
        const uint4* pf = reinterpret_cast<const uint4*>(sp + OFF_PF) + (g & 1) * 128 + t;
        for (int i = 0; i < 16; i++) {
            const uint4 pw0 = pf[i * 8], pw1 = pf[i * 8 + 4];
            mbar_wait(bar_full + 8 * st, par);
            const uint32_t base = sb + st * STAGE_BYTES + va;
            uint32_t v0[4], v1[4], v2[4], v3[4];
            ldsm4t(v0, base);
            ldsm4t(v1, base + 2048);
            ldsm4t(v2, base + 4096);
            ldsm4t(v3, base + 6144);
            mma16816(ca, v0[0], v0[1], v0[2], v0[3], pw0.x, pw0.y);
            mma16816(cb, v1[0], v1[1], v1[2], v1[3], pw0.z, pw0.w);
            mma16816(ca, v2[0], v2[1], v2[2], v2[3], pw1.x, pw1.y);
            mma16816(cb, v3[0], v3[1], v3[2], v3[3], pw1.z, pw1.w);
            __syncwarp();
            if (lane == 0) mbar_arrive(bar_empty + 8 * st);
            if (++st == NSTAGE) { st = 0; par ^= 1; }
            if (i == HPOS && proj && warp < 7) gather_pkts<2, 0>(&sc->h[(pk * 14 + 2 * warp) * 32 + lane], tag, hv);
        }
#pragma unroll
        for (int i = 0; i < 4; i++) ca[i] += cb[i];
        const bool odd = g & 1;
        const float n0 = __shfl_xor_sync(~0u, odd ? ca[0] : ca[1], 4);
        const float n1 = __shfl_xor_sync(~0u, odd ? ca[2] : ca[3], 4);
        const uint32_t w0 = odd ? pack_bf16(n0, ca[1]) : pack_bf16(ca[0], n0);
        const uint32_t w1w = odd ? pack_bf16(n1, ca[3]) : pack_bf16(ca[2], n1);
        if (t == 0) st_pkt16(o_slot, w0, w1w, tag);
    }
    if (proj) {
        constexpr int S35 = 35 % NSTAGE, P35 = (35 / NSTAGE) & 1, S36 = 36 % NSTAGE, P36 = (36 / NSTAGE) & 1,
                      S37 = 37 % NSTAGE, P37 = (37 / NSTAGE) & 1;
        const uint32_t wa0 = pin(sb + (warp * 32 + r + 8 * (mi >> 1)) * 64 + (((mi & 1) ^ ((r >> 1) & 3)) << 4));
        const uint32_t wa1 = wa0 ^ 32u;
        const int e = warp * DM + pc * 32 + lane;
        unsigned long long* accp = pin(&sc->acc[e]);
        __nv_bfloat16* outp = pin(out + e);
        const uint32_t rw = pin(sb + OFF_SC + ((warp * 8 + 2 * t) * 36 + g) * 4), rr = pin(sb + OFF_SC + (warp * 36 + lane) * 4);
        const uint4* op = pin(&sc->o[(pk * 32 + 2 * warp) * 32 + lane]);
        float acm[2][4] = {}, acc[2][2][4] = {};
        const float g0 = misc[2 * t], g1 = misc[2 * t + 1], m0 = misc[8 + 2 * t], m1 = misc[8 + 2 * t + 1];
        uint32_t aa[8][4];
        mbar_wait(bar_full + 8 * S35, P35);
        if (warp < 7) {
#pragma unroll
            for (int ks = 0; ks < 2; ks++) {
                ldsm4t(aa[0], wa0 + S35 * STAGE_BYTES + ks * 1024);
                ldsm4t(aa[1], wa1 + S35 * STAGE_BYTES + ks * 1024);
                mma16816(acm[0], aa[0][0], aa[0][1], aa[0][2], aa[0][3], (uint32_t)hv[ks], (uint32_t)(hv[ks] >> 32));
                mma16816(acm[1], aa[1][0], aa[1][1], aa[1][2], aa[1][3], (uint32_t)hv[ks], (uint32_t)(hv[ks] >> 32));
            }
        }
        unsigned long long ov[4], oh[4];
        {
            const uint32_t tg = *reinterpret_cast<volatile uint32_t*>(sp + OFF_T0) + *reinterpret_cast<volatile uint32_t*>(sp + OFF_SHIFT) + P.gate;
            uint32_t now;
            unsigned n = 0;
            do { asm volatile("mov.u32 %0, %%globaltimer_lo;" : "=r"(now)); } while ((int)(now - tg) < 0 && ++n < TIME_LIMIT);
        }
#pragma unroll
        for (int i = 0; i < 4; i++) ld_pkt16(op + 32 * (i & 1) + 512 * (i >> 1), ov[i], oh[i]);
        int have = 0;
        for (unsigned n = 0;; n++) {
            if (have == 0 && __all_sync(~0u, mbar_test(bar_full + 8 * S36, P36))) {
                have = 1;
#pragma unroll
                for (int i = 0; i < 4; i++) ldsm4t(aa[i], ((i & 1) ? wa1 : wa0) + S36 * STAGE_BYTES + (i >> 1) * 1024);
            }
            if (have == 1 && __all_sync(~0u, mbar_test(bar_full + 8 * S37, P37))) {
                have = 2;
#pragma unroll
                for (int i = 0; i < 4; i++) ldsm4t(aa[4 + i], ((i & 1) ? wa1 : wa0) + S37 * STAGE_BYTES + (i >> 1) * 1024);
            }
            bool need[4], any = false;
#pragma unroll
            for (int i = 0; i < 4; i++) { need[i] = (uint32_t)oh[i] != tag; any |= need[i]; }
            if (!__any_sync(~0u, any)) break;
#pragma unroll
            for (int i = 0; i < 4; i++) reld_pkt16(op + 32 * (i & 1) + 512 * (i >> 1), ov[i], oh[i], need[i]);
            if (n > SPIN_LIMIT) __trap();
        }
        if (have == 0) {
            mbar_wait(bar_full + 8 * S36, P36);
#pragma unroll
            for (int i = 0; i < 4; i++) ldsm4t(aa[i], ((i & 1) ? wa1 : wa0) + S36 * STAGE_BYTES + (i >> 1) * 1024);
        }
#pragma unroll
        for (int i = 0; i < 4; i++)
            mma16816(acc[i & 1][(i >> 1) & 1], aa[i][0], aa[i][1], aa[i][2], aa[i][3], (uint32_t)ov[i >> 1], (uint32_t)(ov[i >> 1] >> 32));
        if (have < 2) {
            mbar_wait(bar_full + 8 * S37, P37);
#pragma unroll
            for (int i = 0; i < 4; i++) ldsm4t(aa[4 + i], ((i & 1) ? wa1 : wa0) + S37 * STAGE_BYTES + (i >> 1) * 1024);
        }
#pragma unroll
        for (int i = 4; i < 8; i++)
            mma16816(acc[i & 1][(i >> 1) & 1], aa[i][0], aa[i][1], aa[i][2], aa[i][3], (uint32_t)ov[i >> 1], (uint32_t)(ov[i >> 1] >> 32));
#pragma unroll
        for (int mt = 0; mt < 2; mt++)
#pragma unroll
            for (int i = 0; i < 4; i++)
                asm volatile("st.shared.f32 [%0], %1;" ::"r"(rw + (16 * mt + 36 * (i & 1) + 8 * (i >> 1)) * 4),
                             "f"(((i & 1) ? g1 : g0) * (acc[mt][0][i] + acc[mt][1][i]) + ((i & 1) ? m1 : m0) * acm[mt][i]) : "memory");
        cons_sync();
        float u[8];
#pragma unroll
        for (int w = 0; w < 8; w++) asm volatile("ld.shared.f32 %0, [%1];" : "=f"(u[w]) : "r"(rr + w * 8 * 36 * 4) : "memory");
        const float v = ((u[0] + u[1]) + (u[2] + u[3])) + ((u[4] + u[5]) + (u[6] + u[7]));
        const uint32_t vmax = __reduce_max_sync(~0u, __float_as_uint(v) & 0x7fffffffu);
        unsigned long long add = acc_encode(v, 1);
        const bool boxed = vmax - 0x37800000u >= 0x45000000u - 0x37800000u;
        asm("{\n.reg .pred p;\nsetp.ne.u32 p, %1, 0;\n@p mov.b64 %0, 17;\n}" : "+l"(add) : "r"((uint32_t)boxed));
        unsigned long long tot;
        asm volatile("atom.relaxed.gpu.global.add.u64 %0, [%1], %2;" : "=l"(tot) : "l"(accp), "l"(add) : "memory");
        if (boxed) st_pkt8(&sc->box[pk * NB * DM + e], __float_as_uint(v), tag);
        tot += add;
        if (((uint32_t)tot & 15u) == 9u) {
            float res = acc_decode(tot);
            if ((uint32_t)tot & 0x1f0u) {
                const uint32_t nbox = ((uint32_t)tot >> 4) & 15u;
                if (nbox == 8u) res = 0.f;
                if (nbox == 8u || ((uint32_t)tot & 256u)) res += misc[8 + warp] * b2v;
                for (unsigned n = 0;; n++) {
                    float sum = 0.f;
                    uint32_t found = 0;
                    for (int k = 0; k < 8; k++) {
                        unsigned long long pv;
                        asm volatile("ld.relaxed.gpu.global.b64 %0, [%1];" : "=l"(pv) : "l"(&sc->box[k * NB * DM + e]) : "memory");
                        if ((uint32_t)(pv >> 32) == tag) { sum += __uint_as_float((uint32_t)pv); found++; }
                    }
                    if (found == nbox) { res += sum; break; }
                    if (n > SPIN_LIMIT) __trap();
                }
            }
            asm volatile("st.global.u16 [%0], %1;" ::"l"(outp), "h"(__bfloat16_as_ushort(__float2bfloat16_rn(res))) : "memory");
            asm volatile("st.global.u64 [%0], 0;" ::"l"(accp) : "memory");
        }
    }
}

__device__ float g_fq[NB * QD], g_fo[NB * QD], g_fh[NB * FF];

__device__ __forceinline__ float ldf(const __nv_bfloat16* p, size_t i) { return __bfloat162float(p[i]); }

__global__ void fb_qh(const __nv_bfloat16* x, const __nv_bfloat16* wq, const __nv_bfloat16* w1, const __nv_bfloat16* b1) {
    const int b = blockIdx.y, n = blockIdx.x * 256 + threadIdx.x;
    float a = 0.f;
    if (n < QD) {
        for (int k = 0; k < DM; k++) a += ldf(x, b * DM + k) * ldf(wq, (size_t)k * QD + n);
        g_fq[b * QD + n] = bf16r(a);
        return;
    }
    const int f = n - QD;
    float m = 0.f, v = 0.f;
    for (int k = 0; k < DM; k++) m += ldf(x, b * DM + k);
    m *= 1.f / DM;
    for (int k = 0; k < DM; k++) { const float d = ldf(x, b * DM + k) - m; v += d * d; }
    const float mb = bf16r(m), sd = bf16r(sqrtf(bf16r(bf16r(v * (1.f / DM)) + 1e-5f)));
    for (int k = 0; k < DM; k++) a += bf16r(bf16r(ldf(x, b * DM + k) - mb) / sd) * ldf(w1, (size_t)k * FF + f);
    const float u = bf16r(bf16r(a) + ldf(b1, f));
    g_fh[b * FF + f] = bf16r(u / (1.f + expf(-1.5957691216057308f * (u + 0.044715f * u * u * u))));
}
__global__ void fb_attn(const __nv_bfloat16* kc, const __nv_bfloat16* vc) {
    __shared__ float sc[WIN];
    const int h = blockIdx.x, b = blockIdx.y, tid = threadIdx.x, lane = tid & 31;
    const size_t base = ((size_t)(b * 8 + h / 2) * SK + (SK - WIN)) * 256;
    for (int k = tid >> 5; k < WIN; k += 8) {
        float a = 0.f;
        for (int d = lane; d < 256; d += 32) a += g_fq[b * QD + h * 256 + d] * ldf(kc, base + (size_t)k * 256 + d);
        for (int o = 16; o; o >>= 1) a += __shfl_xor_sync(~0u, a, o);
        if (lane == 0) sc[k] = bf16r(a) * 0.0625f;
    }
    __syncthreads();
    float m = sc[0], l = 0.f, a = 0.f;
    for (int k = 1; k < WIN; k++) m = fmaxf(m, sc[k]);
    for (int k = 0; k < WIN; k++) l += expf(sc[k] - m);
    for (int k = 0; k < WIN; k++) a += bf16r(expf(sc[k] - m) / l) * ldf(vc, base + (size_t)k * 256 + tid);
    g_fo[b * QD + h * 256 + tid] = bf16r(a);
}
__global__ void fb_out(const __nv_bfloat16* x, const __nv_bfloat16* gw, const __nv_bfloat16* wo, const __nv_bfloat16* w2,
                       const __nv_bfloat16* b2, __nv_bfloat16* out) {
    const int b = blockIdx.y, n = blockIdx.x * 64 + threadIdx.x;
    float gs = 0.f, a = 0.f, c = 0.f;
    for (int k = 0; k < DM; k++) gs += bf16r(ldf(x, b * DM + k) * ldf(gw, k));
    const float gt = bf16r(1.f / (1.f + expf(-bf16r(gs))));
    for (int k = 0; k < QD; k++) a += g_fo[b * QD + k] * ldf(wo, (size_t)k * DM + n);
    for (int k = 0; k < FF; k++) c += g_fh[b * FF + k] * ldf(w2, (size_t)k * DM + n);
    out[b * DM + n] = __float2bfloat16_rn(gt * a + bf16r(1.f - gt) * (c + ldf(b2, n)));
}

typedef CUresult (*EncodeFn)(CUtensorMap*, CUtensorMapDataType, cuuint32_t, void*, const cuuint64_t*, const cuuint64_t*,
                             const cuuint32_t*, const cuuint32_t*, CUtensorMapInterleave, CUtensorMapSwizzle,
                             CUtensorMapL2promotion, CUtensorMapFloatOOBfill);

bool make_map(EncodeFn encode, CUtensorMap* tm, void* base, int rank, const cuuint64_t* dims, const cuuint64_t* strides,
              const cuuint32_t* box, CUtensorMapSwizzle sw, CUtensorMapL2promotion promo) {
    const cuuint32_t es[3] = {1, 1, 1};
    return encode(tm, CU_TENSOR_MAP_DATA_TYPE_BFLOAT16, rank, base, dims, strides, box, es, CU_TENSOR_MAP_INTERLEAVE_NONE, sw,
                  promo, CU_TENSOR_MAP_FLOAT_OOB_FILL_NONE) == CUDA_SUCCESS;
}

}

extern "C" void kernel_launch(void* const* d_in, const int* in_sizes, int n_in, void* d_out, int out_size) {
    (void)in_sizes; (void)n_in; (void)out_size;
    typedef const __nv_bfloat16* cbf;
    static bool init = false, fused = false;
    static EncodeFn encode = nullptr;
    static Scratch* scratch = nullptr;
    static int tau = 0;
    if (!init) {
        init = true;
        void* fn = nullptr;
        cudaDriverEntryPointQueryResult qr;
        cudaGetDriverEntryPoint("cuTensorMapEncodeTiled", &fn, cudaEnableDefault, &qr);
        encode = (EncodeFn)fn;
        cudaGetSymbolAddress((void**)&scratch, g_scratch);
        int dev = 0, khz = 0, bits = 0, clusters = 0;
        cudaGetDevice(&dev);
        cudaDeviceGetAttribute(&khz, cudaDevAttrMemoryClockRate, dev);
        cudaDeviceGetAttribute(&bits, cudaDevAttrGlobalMemoryBusWidth, dev);
        const double peak = 2.0 * khz * 1e-6 * bits / 8.0;
        tau = peak > 0 ? (int)(NCTA * (double)STAGE_BYTES / (PACE_FRAC * peak) + 0.5) : 0;
        if (cudaFuncSetAttribute(fused_kernel, cudaFuncAttributeMaxDynamicSharedMemorySize, SMEM_BYTES) == cudaSuccess) {
            cudaLaunchConfig_t cfg = {};
            cfg.gridDim = dim3(NCTA); cfg.blockDim = dim3(NTHREADS); cfg.dynamicSmemBytes = SMEM_BYTES;
            cudaLaunchAttribute at;
            at.id = cudaLaunchAttributeClusterDimension;
            at.val.clusterDim.x = 2; at.val.clusterDim.y = 1; at.val.clusterDim.z = 1;
            cfg.attrs = &at; cfg.numAttrs = 1;
            if (cudaOccupancyMaxActiveClusters(&clusters, fused_kernel, &cfg) != cudaSuccess) clusters = 0;
        }
        fused = encode && scratch && clusters >= NCTA / 2;
        (void)cudaGetLastError();
    }
    CUtensorMap tmK, tmV, tmWo, tmW2, tmWq, tmW1;
    bool ok = fused;
    if (ok) {
        const cuuint64_t dimsKV[3] = {64, (cuuint64_t)64 * SK, 4}, strKV[2] = {512, 128};
        const cuuint32_t boxK[3] = {64, 32, 4}, boxV[3] = {64, 64, 2};
        const cuuint64_t dimsO[2] = {DM, QD}, dims2[2] = {DM, FF}, strO[1] = {DM * 2};
        const cuuint32_t boxO[2] = {32, 256}, box2[2] = {32, 224};
        const cuuint64_t dimsQ[2] = {QD, DM}, dims1[2] = {FF, DM}, strQ[1] = {QD * 2}, str1[1] = {FF * 2};
        const cuuint32_t boxQ[2] = {32, 256}, box1[2] = {16, 256};
        ok = make_map(encode, &tmK, d_in[1], 3, dimsKV, strKV, boxK, CU_TENSOR_MAP_SWIZZLE_128B, CU_TENSOR_MAP_L2_PROMOTION_L2_256B) &&
             make_map(encode, &tmV, d_in[2], 3, dimsKV, strKV, boxV, CU_TENSOR_MAP_SWIZZLE_128B, CU_TENSOR_MAP_L2_PROMOTION_L2_256B) &&
             make_map(encode, &tmWo, d_in[4], 2, dimsO, strO, boxO, CU_TENSOR_MAP_SWIZZLE_64B, CU_TENSOR_MAP_L2_PROMOTION_NONE) &&
             make_map(encode, &tmW2, d_in[8], 2, dims2, strO, box2, CU_TENSOR_MAP_SWIZZLE_64B, CU_TENSOR_MAP_L2_PROMOTION_NONE) &&
             make_map(encode, &tmWq, d_in[3], 2, dimsQ, strQ, boxQ, CU_TENSOR_MAP_SWIZZLE_64B, CU_TENSOR_MAP_L2_PROMOTION_NONE) &&
             make_map(encode, &tmW1, d_in[6], 2, dims1, str1, box1, CU_TENSOR_MAP_SWIZZLE_32B, CU_TENSOR_MAP_L2_PROMOTION_NONE);
    }
    if (!ok) {
        fb_qh<<<dim3((QD + FF) / 256, NB), 256>>>((cbf)d_in[0], (cbf)d_in[3], (cbf)d_in[6], (cbf)d_in[7]);
        fb_attn<<<dim3(16, NB), 256>>>((cbf)d_in[1], (cbf)d_in[2]);
        fb_out<<<dim3(DM / 64, NB), 64>>>((cbf)d_in[0], (cbf)d_in[10], (cbf)d_in[4], (cbf)d_in[8], (cbf)d_in[9], (__nv_bfloat16*)d_out);
        return;
    }
    Params P;
    P.sc = scratch;
    P.wq = (cbf)d_in[3]; P.x = (cbf)d_in[0]; P.gate_w = (cbf)d_in[10]; P.b1 = (cbf)d_in[7]; P.b2 = (cbf)d_in[9];
    P.out = (__nv_bfloat16*)d_out;
    P.tau = tau;
    P.lead = (int)(PACE_LEAD * tau);
    P.gate = (int)(PACE_GATE * P.tau) - P.lead;
    P.a16 = PACE_GAIN16;
    P.target = (int)(PACE_BACKLOG * P.tau);
    fused_kernel<<<NCTA, NTHREADS, SMEM_BYTES>>>(P, tmWq, tmK, tmV, tmW1, tmW2, tmWo);
}
```
